```python
import torch

def _softmax(x, axis=-1):
    return torch.softmax(x, dim=axis)

def _gelu(x):
    return torch.nn.functional.gelu(x, approximate='tanh')

def _silu(x):
    return torch.nn.functional.silu(x)

def _sigmoid(x):
    return torch.sigmoid(x)

def _layernorm(x, axis=-1, eps=1e-05):
    m = x.mean(dim=axis, keepdim=True)
    v = x.var(dim=axis, keepdim=True, unbiased=False)
    return (x - m) / torch.sqrt(v + eps)

def _scatter_add(tgt, idx, src, axis=0):
    return tgt.clone().index_add_(axis, idx, src)

def _segment_sum(src, seg, n):
    out = torch.zeros((n,) + src.shape[1:], dtype=src.dtype)
    return out.index_add_(0, seg, src)

def _pad(x, pw):
    flat = tuple((v for pair in reversed(pw) for v in pair))
    return torch.nn.functional.pad(x, flat)
kernel_name = 'concat_heads__spectral_gfnet__memory_aug_recurrent_mem_tr__prompt'

def setup_inputs():

    _w = lambda a: (lambda t: t.to(torch.bfloat16) if t.is_floating_point() else t)(torch.as_tensor(a))

    def _A_setup():
        B, S, D = (1, 2048, 1024)
        Df = D // 2 + 1
        return {'x': _w((lambda *s: torch.randn(*s, dtype=torch.bfloat16) * 0.05)(B, S, D)), 'w_r': _w((lambda *s: torch.randn(*s, dtype=torch.bfloat16) * 3.2)(S, Df) * 0.02), 'w_i': _w((lambda *s: torch.randn(*s, dtype=torch.bfloat16) * 3.2)(S, Df) * 0.02)}
    _A_in = _A_setup()

    def _B_setup():
        B, S, Dm = (1, 2048, 1024)
        H, Dh = (32, 128)
        M, seg = (8, 32)
        seg = min(seg, S)
        S = S // seg * seg
        return {'x': _w((lambda *s: torch.randn(*s, dtype=torch.bfloat16) * 0.05)(B, S, Dm)), 'mem0': _w((lambda *s: torch.randn(*s, dtype=torch.bfloat16) * 0.4)(B, M, Dm)), 'Wq': _w((lambda *s: torch.randn(*s, dtype=torch.bfloat16) * 6.4)(Dm, H, Dh) * Dm ** (-0.5)), 'Wk': _w((lambda *s: torch.randn(*s, dtype=torch.bfloat16) * 6.4)(Dm, H, Dh) * Dm ** (-0.5)), 'Wv': _w((lambda *s: torch.randn(*s, dtype=torch.bfloat16) * 0.4)(Dm, H, Dh) * Dm ** (-0.5)), 'Wo': _w((lambda *s: torch.randn(*s, dtype=torch.bfloat16) * 0.4)(H, Dh, Dm) * (H * Dh) ** (-0.5)), 'seg_len': seg}
    _B_in = _B_setup()
    return {'A_x': _A_in['x'], 'A_w_r': _A_in['w_r'], 'A_w_i': _A_in['w_i'], 'B_x': _B_in['x'], 'B_mem0': _B_in['mem0'], 'B_Wq': _B_in['Wq'], 'B_Wk': _B_in['Wk'], 'B_Wv': _B_in['Wv'], 'B_Wo': _B_in['Wo'], 'B_seg_len': _B_in['seg_len']}

def reference(A_x, A_w_r, A_w_i, B_x, B_mem0, B_Wq, B_Wk, B_Wv, B_Wo, B_seg_len):

    def _A_ref(x, w_r, w_i):
        B, S, D = x.shape
        X = (lambda x, axes=(-2, -1): torch.fft.rfft2(x.float(), dim=axes))(x, axes=(-2, -1))
        W = w_r + 1j * w_i
        X = X * W
        y = (lambda x, s, axes=(-2, -1): torch.fft.irfft2(x, s=s, dim=axes).to(torch.bfloat16))(X, (S, D), axes=(-2, -1))
        return y

    def _B_ref(x, mem0, Wq, Wk, Wv, Wo, seg_len):
        B, S, Dm = x.shape
        H, Dh = (Wq.shape[1], Wq.shape[2])
        M = mem0.shape[1]
        scale = Dh ** (-0.5)
        n_seg = S // seg_len
        L = M + seg_len
        idx = torch.arange(L)
        mask = (idx[:, None] < M) | (idx[:, None] >= idx[None, :])
        mem = mem0
        outs = []
        for s in range(n_seg):
            xs = x[:, s * seg_len:(s + 1) * seg_len, :].clone()
            h = torch.concatenate([mem, xs], axis=1)
            q = torch.einsum('btd,dhe->bhte', h, Wq)
            k = torch.einsum('btd,dhe->bhte', h, Wk)
            v = torch.einsum('btd,dhe->bhte', h, Wv)
            scores = torch.einsum('bhqe,bhke->bhqk', q, k) * scale
            scores = torch.where(mask[None, None], scores, -1000000000.0)
            p = _softmax(scores, axis=-1)
            o = torch.einsum('bhqk,bhke->bhqe', p, v)
            o = torch.einsum('bhte,hed->btd', o, Wo)
            mem = o[:, :M, :].clone()
            outs.append(o[:, M:, :])
        return torch.concatenate(outs, axis=1)
    a = _A_ref(A_x, A_w_r, A_w_i)
    b = _B_ref(B_x, B_mem0, B_Wq, B_Wk, B_Wv, B_Wo, B_seg_len)
    return torch.concatenate([a, b], axis=-1)
```

```cpp
#include <cuda_runtime.h>
#include <cuda_bf16.h>
#include <cuda.h>
#include <stdint.h>

typedef __nv_bfloat16 bf16;

constexpr int S_LEN = 2048, DM = 1024, NH = 32, DH = 128, HD = 4096, NMEM = 8, SEG = 32, NSEG = 64;
constexpr int OUT_LD = 2048;
constexpr uint32_t SENT = 0xFFFFFFFFu;

__device__ __forceinline__ uint32_t smem_u32(const void* p) { return (uint32_t)__cvta_generic_to_shared(p); }
__device__ __forceinline__ void mbar_init(uint32_t bar, uint32_t cnt) {
  asm volatile("mbarrier.init.shared::cta.b64 [%0], %1;" ::"r"(bar), "r"(cnt) : "memory");
}
__device__ __forceinline__ void mbar_expect_tx(uint32_t bar, uint32_t bytes) {
  asm volatile("mbarrier.arrive.expect_tx.shared::cta.b64 _, [%0], %1;" ::"r"(bar), "r"(bytes) : "memory");
}
__device__ __forceinline__ void mbar_arrive(uint32_t bar) {
  asm volatile("mbarrier.arrive.shared::cta.b64 _, [%0];" ::"r"(bar) : "memory");
}
__device__ __forceinline__ void mbar_arrive_tx_if(uint32_t bar, uint32_t bytes, uint32_t cond) {
  asm volatile("{.reg .pred q; setp.ne.u32 q, %2, 0; @q mbarrier.arrive.expect_tx.shared::cta.b64 _, [%0], %1;}" ::"r"(bar), "r"(bytes), "r"(cond) : "memory");
}
__device__ __forceinline__ void mbar_arrive_cluster(uint32_t bar_cluster_addr) {
  asm volatile("mbarrier.arrive.shared::cluster.b64 _, [%0];" ::"r"(bar_cluster_addr) : "memory");
}
__device__ __forceinline__ bool mbar_try(uint32_t bar, uint32_t par) {
  uint32_t ok;
  asm volatile("{.reg .pred p; mbarrier.try_wait.parity.shared::cta.b64 p, [%1], %2; selp.u32 %0, 1, 0, p;}"
               : "=r"(ok) : "r"(bar), "r"(par) : "memory");
  return ok;
}
#define FAIL(id) __trap()
__device__ __forceinline__ void mbar_wait(uint32_t bar, uint32_t par) {
  if (__builtin_expect(!mbar_try(bar, par), 0)) {
    int it = 0;
    while (!mbar_try(bar, par)) { if (++it > (1 << 18)) FAIL((bar & 255) + par * 1000); }
  }
}
__device__ __forceinline__ void tma2d(uint32_t dst, const CUtensorMap* tm, int c0, int c1, uint32_t bar) {
  asm volatile("cp.async.bulk.tensor.2d.shared::cluster.global.mbarrier::complete_tx::bytes [%0], [%1, {%3, %4}], [%2];"
               ::"r"(dst), "l"(tm), "r"(bar), "r"(c0), "r"(c1) : "memory");
}
__device__ __forceinline__ void tma2d_ef(uint32_t dst, const CUtensorMap* tm, int c0, int c1, uint32_t bar) {
  asm volatile("cp.async.bulk.tensor.2d.shared::cluster.global.mbarrier::complete_tx::bytes.L2::cache_hint [%0], [%1, {%3, %4}], [%2], %5;"
               ::"r"(dst), "l"(tm), "r"(bar), "r"(c0), "r"(c1), "l"(0x12F0000000000000ull) : "memory");
}
__device__ __forceinline__ void tma2d_mc(uint32_t dst, const CUtensorMap* tm, int c0, int c1, uint32_t bar, uint16_t mask) {
  asm volatile("cp.async.bulk.tensor.2d.shared::cluster.global.mbarrier::complete_tx::bytes.multicast::cluster [%0], [%1, {%3, %4}], [%2], %5;"
               ::"r"(dst), "l"(tm), "r"(bar), "r"(c0), "r"(c1), "h"(mask) : "memory");
}
__device__ __forceinline__ void tma2d_store(const CUtensorMap* tm, uint32_t src, int c0, int c1) {
  asm volatile("cp.async.bulk.tensor.2d.global.shared::cta.bulk_group [%0, {%2, %3}], [%1];"
               ::"l"(tm), "r"(src), "r"(c0), "r"(c1) : "memory");
}
__device__ __forceinline__ uint32_t mapa(uint32_t a, uint32_t r) {
  uint32_t o; asm("mapa.shared::cluster.u32 %0, %1, %2;" : "=r"(o) : "r"(a), "r"(r)); return o;
}
__device__ __forceinline__ void st_async8(uint32_t addr, float a, float b, uint32_t bar) {
  asm volatile("st.async.weak.shared::cluster.mbarrier::complete_tx::bytes.v2.f32 [%0], {%1, %2}, [%3];"
               ::"r"(addr), "f"(a), "f"(b), "r"(bar) : "memory");
}
__device__ __forceinline__ void st_async8_if(uint32_t addr, float a, float b, uint32_t bar, uint32_t cond) {
  asm volatile("{.reg .pred q; setp.ne.u32 q, %4, 0; @q st.async.weak.shared::cluster.mbarrier::complete_tx::bytes.v2.f32 [%0], {%1, %2}, [%3];}"
               ::"r"(addr), "f"(a), "f"(b), "r"(bar), "r"(cond) : "memory");
}
__device__ __forceinline__ void st_async16(uint32_t addr, const float* v, uint32_t bar) {
  asm volatile("st.async.weak.shared::cluster.mbarrier::complete_tx::bytes.v4.f32 [%0], {%1, %2, %3, %4}, [%5];"
               ::"r"(addr), "f"(v[0]), "f"(v[1]), "f"(v[2]), "f"(v[3]), "r"(bar) : "memory");
}
__device__ __forceinline__ void st_async4(uint32_t addr, float a, uint32_t bar) {
  asm volatile("st.async.weak.shared::cluster.mbarrier::complete_tx::bytes.f32 [%0], %1, [%2];"
               ::"r"(addr), "f"(a), "r"(bar) : "memory");
}
__device__ __forceinline__ void cluster_sync() {
  asm volatile("barrier.cluster.arrive.release.aligned; barrier.cluster.wait.acquire.aligned;" ::: "memory");
}
__device__ __forceinline__ void bar_sync(int id, int n) { asm volatile("bar.sync %0, %1;" ::"r"(id), "r"(n) : "memory"); }
__device__ __forceinline__ void ldsm4(uint32_t& r0, uint32_t& r1, uint32_t& r2, uint32_t& r3, uint32_t a) {
  asm volatile("ldmatrix.sync.aligned.m8n8.x4.shared.b16 {%0,%1,%2,%3}, [%4];"
               : "=r"(r0), "=r"(r1), "=r"(r2), "=r"(r3) : "r"(a) : "memory");
}
__device__ __forceinline__ void ldsm4t(uint32_t& r0, uint32_t& r1, uint32_t& r2, uint32_t& r3, uint32_t a) {
  asm volatile("ldmatrix.sync.aligned.m8n8.x4.trans.shared.b16 {%0,%1,%2,%3}, [%4];"
               : "=r"(r0), "=r"(r1), "=r"(r2), "=r"(r3) : "r"(a) : "memory");
}
__device__ __forceinline__ void stsm4(uint32_t a, uint32_t r0, uint32_t r1, uint32_t r2, uint32_t r3) {
  asm volatile("stmatrix.sync.aligned.m8n8.x4.shared.b16 [%0], {%1,%2,%3,%4};"
               ::"r"(a), "r"(r0), "r"(r1), "r"(r2), "r"(r3) : "memory");
}
__device__ __forceinline__ void stsm1(uint32_t a, uint32_t r0) {
  asm volatile("stmatrix.sync.aligned.m8n8.x1.shared.b16 [%0], {%1};" ::"r"(a), "r"(r0) : "memory");
}
__device__ __forceinline__ void mma16816(float* d, uint32_t a0, uint32_t a1, uint32_t a2, uint32_t a3, uint32_t b0, uint32_t b1) {
  asm volatile("mma.sync.aligned.m16n8k16.row.col.f32.bf16.bf16.f32 {%0,%1,%2,%3}, {%4,%5,%6,%7}, {%8,%9}, {%0,%1,%2,%3};"
               : "+f"(d[0]), "+f"(d[1]), "+f"(d[2]), "+f"(d[3])
               : "r"(a0), "r"(a1), "r"(a2), "r"(a3), "r"(b0), "r"(b1));
}
__device__ __forceinline__ void mma1688(float* d, uint32_t a0, uint32_t a1, uint32_t b0) {
  asm volatile("mma.sync.aligned.m16n8k8.row.col.f32.bf16.bf16.f32 {%0,%1,%2,%3}, {%4,%5}, {%6}, {%0,%1,%2,%3};"
               : "+f"(d[0]), "+f"(d[1]), "+f"(d[2]), "+f"(d[3]) : "r"(a0), "r"(a1), "r"(b0));
}
__device__ __forceinline__ uint32_t pack_bf16(float lo, float hi) {
  uint32_t r; asm("cvt.rn.bf16x2.f32 %0, %1, %2;" : "=r"(r) : "f"(hi), "f"(lo)); return r;
}
__device__ __forceinline__ uint4 ld_relaxed16(const void* p) {
  uint4 v;
  asm volatile("ld.relaxed.gpu.global.v4.u32 {%0,%1,%2,%3}, [%4];" : "=r"(v.x), "=r"(v.y), "=r"(v.z), "=r"(v.w) : "l"(p) : "memory");
  return v;
}
__device__ __forceinline__ uint4 ld_relaxed16b(const void* p) {
  uint4 v;
  asm volatile("ld.relaxed.gpu.global.v4.b32 {%0,%1,%2,%3}, [%4];" : "=r"(v.x), "=r"(v.y), "=r"(v.z), "=r"(v.w) : "l"(p) : "memory");
  return v;
}
__device__ __forceinline__ uint32_t ld_relaxed4(const void* p) {
  uint32_t v; asm volatile("ld.relaxed.gpu.global.u32 %0, [%1];" : "=r"(v) : "l"(p) : "memory"); return v;
}
__device__ __forceinline__ void st_relaxed4(void* p, uint32_t v) {
  asm volatile("st.relaxed.gpu.global.u32 [%0], %1;" ::"l"(p), "r"(v) : "memory");
}
__device__ __forceinline__ void st_relaxed4_if(void* p, uint32_t v, uint32_t cond) {
  asm volatile("{.reg .pred q; setp.ne.u32 q, %2, 0; @q st.relaxed.gpu.global.u32 [%0], %1;}" ::"l"(p), "r"(v), "r"(cond) : "memory");
}
__device__ __forceinline__ void sts16(uint32_t a, uint4 v) {
  asm volatile("st.shared.v4.u32 [%0], {%1,%2,%3,%4};" ::"r"(a), "r"(v.x), "r"(v.y), "r"(v.z), "r"(v.w) : "memory");
}
__device__ __forceinline__ void sts4f(uint32_t a, float v) { asm volatile("st.shared.f32 [%0], %1;" ::"r"(a), "f"(v) : "memory"); }
__device__ __forceinline__ void sts8f(uint32_t a, float x, float y) { asm volatile("st.shared.v2.f32 [%0], {%1,%2};" ::"r"(a), "f"(x), "f"(y) : "memory"); }
__device__ __forceinline__ float lds4f(uint32_t a) { float v; asm volatile("ld.shared.f32 %0, [%1];" : "=f"(v) : "r"(a) : "memory"); return v; }
__device__ __forceinline__ float2 lds8f(uint32_t a) { float2 v; asm volatile("ld.shared.v2.f32 {%0,%1}, [%2];" : "=f"(v.x), "=f"(v.y) : "r"(a) : "memory"); return v; }
__device__ __forceinline__ uint32_t lds4(uint32_t a) { uint32_t v; asm volatile("ld.shared.u32 %0, [%1];" : "=r"(v) : "r"(a) : "memory"); return v; }
__device__ __forceinline__ uint2 lds8(uint32_t a) { uint2 v; asm volatile("ld.shared.v2.u32 {%0,%1}, [%2];" : "=r"(v.x), "=r"(v.y) : "r"(a) : "memory"); return v; }
__device__ __forceinline__ uint32_t umax4(uint4 v) { return max(max(v.x, v.y), max(v.z, v.w)); }
__device__ __forceinline__ float ex2(float x) { float y; asm("ex2.approx.ftz.f32 %0, %1;" : "=f"(y) : "f"(x)); return y; }

__device__ __forceinline__ void fence_gpu() { asm volatile("fence.acq_rel.gpu;" ::: "memory"); }
#define WG_FENCE() asm volatile("wgmma.fence.sync.aligned;" ::: "memory")
#define WG_COMMIT() asm volatile("wgmma.commit_group.sync.aligned;" ::: "memory")
#define WG_WAIT(n) asm volatile("wgmma.wait_group.sync.aligned " #n ";" ::: "memory")
__device__ __forceinline__ uint64_t mk_desc(uint32_t addr, uint32_t lbo, uint32_t sbo) {
  return (uint64_t)((addr >> 4) & 0x3FFF) | ((uint64_t)(lbo >> 4) << 16) | ((uint64_t)(sbo >> 4) << 32) | ((uint64_t)1 << 62);
}
__device__ __forceinline__ void stsm4t(uint32_t a, uint32_t r0, uint32_t r1, uint32_t r2, uint32_t r3) {
  asm volatile("stmatrix.sync.aligned.m8n8.x4.trans.shared.b16 [%0], {%1,%2,%3,%4};"
               ::"r"(a), "r"(r0), "r"(r1), "r"(r2), "r"(r3) : "memory");
}
__device__ __forceinline__ void sts16f(uint32_t a, float x, float y, float z, float w) {
  asm volatile("st.shared.v4.f32 [%0], {%1,%2,%3,%4};" ::"r"(a), "f"(x), "f"(y), "f"(z), "f"(w) : "memory");
}
__device__ __forceinline__ float4 lds16f(uint32_t a) {
  float4 v; asm volatile("ld.shared.v4.f32 {%0,%1,%2,%3}, [%4];" : "=f"(v.x), "=f"(v.y), "=f"(v.z), "=f"(v.w) : "r"(a) : "memory"); return v;
}
__device__ __forceinline__ uint4 lds16(uint32_t a) {
  uint4 v; asm volatile("ld.shared.v4.u32 {%0,%1,%2,%3}, [%4];" : "=r"(v.x), "=r"(v.y), "=r"(v.z), "=r"(v.w) : "r"(a) : "memory"); return v;
}
__device__ __forceinline__ uint2 ld_relaxed8(const void* p) {
  uint2 v; asm volatile("ld.relaxed.gpu.global.v2.u32 {%0,%1}, [%2];" : "=r"(v.x), "=r"(v.y) : "l"(p) : "memory"); return v;
}
__device__ __forceinline__ void st_relaxed8(void* p, uint32_t a, uint32_t b) {
  asm volatile("st.relaxed.gpu.global.v2.u32 [%0], {%1,%2};" ::"l"(p), "r"(a), "r"(b) : "memory");
}
__device__ __forceinline__ void st_relaxed16(void* p, uint4 v) {
  asm volatile("st.relaxed.gpu.global.v4.u32 [%0], {%1,%2,%3,%4};" ::"l"(p), "r"(v.x), "r"(v.y), "r"(v.z), "r"(v.w) : "memory");
}
__device__ __forceinline__ void bar_arrive(int id, int n) { asm volatile("bar.arrive %0, %1;" ::"r"(id), "r"(n) : "memory"); }
template <typename T> __device__ __forceinline__ void keep32(T& x) { asm volatile("" : "+r"(x)); }
template <typename T> __device__ __forceinline__ void keep64(T& x) { asm volatile("" : "+l"(x)); }
#define ACC16(d) "+f"(d[0]), "+f"(d[1]), "+f"(d[2]), "+f"(d[3]), "+f"(d[4]), "+f"(d[5]), "+f"(d[6]), "+f"(d[7]), \
                 "+f"(d[8]), "+f"(d[9]), "+f"(d[10]), "+f"(d[11]), "+f"(d[12]), "+f"(d[13]), "+f"(d[14]), "+f"(d[15])
#define OUT16(d) "=f"(d[0]), "=f"(d[1]), "=f"(d[2]), "=f"(d[3]), "=f"(d[4]), "=f"(d[5]), "=f"(d[6]), "=f"(d[7]), \
                 "=f"(d[8]), "=f"(d[9]), "=f"(d[10]), "=f"(d[11]), "=f"(d[12]), "=f"(d[13]), "=f"(d[14]), "=f"(d[15])
template <int ACC> __device__ __forceinline__ void wg_rs32(float* d, const uint32_t* a, uint64_t db) {
  if (ACC == 2)
    asm volatile("wgmma.mma_async.sync.aligned.m64n32k16.f32.bf16.bf16 "
                 "{%0,%1,%2,%3,%4,%5,%6,%7,%8,%9,%10,%11,%12,%13,%14,%15}, {%16,%17,%18,%19}, %20, 0, 1, 1, 0;"
                 : ACC16(d) : "r"(a[0]), "r"(a[1]), "r"(a[2]), "r"(a[3]), "l"(db));
  else if (ACC)
    asm volatile("wgmma.mma_async.sync.aligned.m64n32k16.f32.bf16.bf16 "
                 "{%0,%1,%2,%3,%4,%5,%6,%7,%8,%9,%10,%11,%12,%13,%14,%15}, {%16,%17,%18,%19}, %20, 1, 1, 1, 0;"
                 : ACC16(d) : "r"(a[0]), "r"(a[1]), "r"(a[2]), "r"(a[3]), "l"(db));
  else
    asm volatile("wgmma.mma_async.sync.aligned.m64n32k16.f32.bf16.bf16 "
                 "{%0,%1,%2,%3,%4,%5,%6,%7,%8,%9,%10,%11,%12,%13,%14,%15}, {%16,%17,%18,%19}, %20, 0, 1, 1, 0;"
                 : OUT16(d) : "r"(a[0]), "r"(a[1]), "r"(a[2]), "r"(a[3]), "l"(db));
}
__device__ __forceinline__ void acc_fence16(float* d) { asm volatile("" : ACC16(d)::"memory"); }
__device__ __forceinline__ void wg_ss32(float* d, uint64_t da, uint64_t db) {
  asm volatile("wgmma.mma_async.sync.aligned.m64n32k16.f32.bf16.bf16 "
               "{%0,%1,%2,%3,%4,%5,%6,%7,%8,%9,%10,%11,%12,%13,%14,%15}, %16, %17, 1, 1, 1, 1, 0;"
               : ACC16(d) : "l"(da), "l"(db));
}
__device__ __forceinline__ void wg_ss32z(float* d, uint64_t da, uint64_t db) {
  asm volatile("wgmma.mma_async.sync.aligned.m64n32k16.f32.bf16.bf16 "
               "{%0,%1,%2,%3,%4,%5,%6,%7,%8,%9,%10,%11,%12,%13,%14,%15}, %16, %17, 0, 1, 1, 1, 0;"
               : OUT16(d) : "l"(da), "l"(db));
}

#define STAMP(i)

__device__ __forceinline__ void wgmma_m64n128_ss_tb(float* d, uint64_t da, uint64_t db) {
  asm volatile(
      "wgmma.mma_async.sync.aligned.m64n128k16.f32.bf16.bf16 "
      "{%0,%1,%2,%3,%4,%5,%6,%7,%8,%9,%10,%11,%12,%13,%14,%15,%16,%17,%18,%19,%20,%21,%22,%23,%24,%25,%26,%27,%28,%29,%30,%31,"
      "%32,%33,%34,%35,%36,%37,%38,%39,%40,%41,%42,%43,%44,%45,%46,%47,%48,%49,%50,%51,%52,%53,%54,%55,%56,%57,%58,%59,%60,%61,%62,%63},"
      "%64,%65,1,1,1,0,1;"
      : "+f"(d[0]), "+f"(d[1]), "+f"(d[2]), "+f"(d[3]), "+f"(d[4]), "+f"(d[5]), "+f"(d[6]), "+f"(d[7]), "+f"(d[8]), "+f"(d[9]),
        "+f"(d[10]), "+f"(d[11]), "+f"(d[12]), "+f"(d[13]), "+f"(d[14]), "+f"(d[15]), "+f"(d[16]), "+f"(d[17]), "+f"(d[18]), "+f"(d[19]),
        "+f"(d[20]), "+f"(d[21]), "+f"(d[22]), "+f"(d[23]), "+f"(d[24]), "+f"(d[25]), "+f"(d[26]), "+f"(d[27]), "+f"(d[28]), "+f"(d[29]),
        "+f"(d[30]), "+f"(d[31]), "+f"(d[32]), "+f"(d[33]), "+f"(d[34]), "+f"(d[35]), "+f"(d[36]), "+f"(d[37]), "+f"(d[38]), "+f"(d[39]),
        "+f"(d[40]), "+f"(d[41]), "+f"(d[42]), "+f"(d[43]), "+f"(d[44]), "+f"(d[45]), "+f"(d[46]), "+f"(d[47]), "+f"(d[48]), "+f"(d[49]),
        "+f"(d[50]), "+f"(d[51]), "+f"(d[52]), "+f"(d[53]), "+f"(d[54]), "+f"(d[55]), "+f"(d[56]), "+f"(d[57]), "+f"(d[58]), "+f"(d[59]),
        "+f"(d[60]), "+f"(d[61]), "+f"(d[62]), "+f"(d[63])
      : "l"(da), "l"(db));
}

constexpr int G_STAGES = 4;
constexpr int G_STAGE_BYTES = 32768;
constexpr int G_SMEM = G_STAGES * G_STAGE_BYTES + 128;

__global__ void __launch_bounds__(288, 2)
gemm_kernel(const __grid_constant__ CUtensorMap tmA, const __grid_constant__ CUtensorMap tmB0,
            const __grid_constant__ CUtensorMap tmB1, const __grid_constant__ CUtensorMap tmB2,
            const __grid_constant__ CUtensorMap tmC, int nb_per, int kblocks, int c_col0, const int* done) {
  extern __shared__ __align__(1024) uint8_t smem_raw[];
  const uint32_t sb = smem_u32(smem_raw);
  if (sb & 1023) __trap();
  const uint32_t bars = sb + G_STAGES * G_STAGE_BYTES;
  const int tid = threadIdx.x, wg = tid >> 7;
  asm volatile("griddepcontrol.launch_dependents;" ::: "memory");
  uint32_t rank; asm("mov.u32 %0, %%cluster_ctarank;" : "=r"(rank));
  const int nt = blockIdx.x, mt = blockIdx.y;
  const int bsel = nt / nb_per, n0 = (nt - bsel * nb_per) * 128;
  const CUtensorMap* tb = bsel == 0 ? &tmB0 : (bsel == 1 ? &tmB1 : &tmB2);
  if (tid == 256) {
    for (int i = 0; i < G_STAGES; i++) { mbar_init(bars + i * 8, 1); mbar_init(bars + (G_STAGES + i) * 8, 4); }
    asm volatile("fence.mbarrier_init.release.cluster;" ::: "memory");
    asm volatile("fence.proxy.async;" ::: "memory");
    for (int kb = 0; kb < G_STAGES; kb++) {
      const uint32_t b = sb + kb * G_STAGE_BYTES + 16384, fb = bars + kb * 8;
      mbar_expect_tx(fb, G_STAGE_BYTES);
      tma2d(b, tb, n0, kb * 64, fb);
      tma2d(b + 8192, tb, n0 + 64, kb * 64, fb);
    }
    for (int i = 0; i < (1 << 22); i++) {
      int v; asm volatile("ld.acquire.gpu.global.s32 %0, [%1];" : "=r"(v) : "l"(done) : "memory");
      if (v == 255) break;
    }
    asm volatile("fence.proxy.async;" ::: "memory");
  }
  __syncwarp();
  cluster_sync();
  if (wg == 2) {
    if (tid == 256) {
      STAMP(3);
      for (int kb = 0; kb < kblocks; kb++) {
        const int st = kb % G_STAGES, ph = (kb / G_STAGES) & 1;
        const uint32_t a = sb + st * G_STAGE_BYTES, b = a + 16384, fb = bars + st * 8;
        if (kb >= G_STAGES) { mbar_wait(bars + (G_STAGES + st) * 8, ph ^ 1); mbar_expect_tx(fb, G_STAGE_BYTES); }
        tma2d_mc(a + rank * 8192, &tmA, kb * 64, mt * 128 + rank * 64, fb, (uint16_t)3);
        if (kb >= G_STAGES) { tma2d(b, tb, n0, kb * 64, fb); tma2d(b + 8192, tb, n0 + 64, kb * 64, fb); }
      }
    }
  } else {
    const int cw = wg;
    float acc[64];
#pragma unroll
    for (int i = 0; i < 64; i++) acc[i] = 0.f;
    for (int kb = 0; kb < kblocks; kb++) {
      const int st = kb % G_STAGES, ph = (kb / G_STAGES) & 1;
      mbar_wait(bars + st * 8, ph);
      const uint32_t a = sb + st * G_STAGE_BYTES + cw * 8192, b = sb + st * G_STAGE_BYTES + 16384;
      const uint64_t da = mk_desc(a, 16, 1024), db = mk_desc(b, 8192, 1024);
      WG_FENCE();
#pragma unroll
      for (int k = 0; k < 4; k++) wgmma_m64n128_ss_tb(acc, da + k * 2, db + k * 128);
      WG_COMMIT();
      WG_WAIT(0);
      if (kb + G_STAGES < kblocks && (tid & 127) < 2) mbar_arrive_cluster(mapa(bars + (G_STAGES + st) * 8, tid & 1));
    }
    WG_WAIT(0);
    bar_sync(1, 256);
    const int w4 = (tid >> 5) & 3, lane = tid & 31;
    const uint32_t cbuf = sb + cw * 16384;
    const int row = w4 * 16 + (lane & 7) + ((lane >> 3) & 1) * 8;
#pragma unroll
    for (int j = 0; j < 8; j++) {
      const int chunk = (j & 3) * 2 + (lane >> 4);
      const uint32_t ad = cbuf + (j >> 2) * 8192 + row * 128 + ((chunk ^ (row & 7)) << 4);
      stsm4(ad, pack_bf16(acc[j * 8 + 0], acc[j * 8 + 1]), pack_bf16(acc[j * 8 + 2], acc[j * 8 + 3]),
            pack_bf16(acc[j * 8 + 4], acc[j * 8 + 5]), pack_bf16(acc[j * 8 + 6], acc[j * 8 + 7]));
    }
    asm volatile("fence.proxy.async.shared::cta;" ::: "memory");
    bar_sync(2 + cw, 128);
    if ((tid & 127) == 0) {
      tma2d_store(&tmC, cbuf, c_col0 + nt * 128, mt * 128 + cw * 64);
      tma2d_store(&tmC, cbuf + 8192, c_col0 + nt * 128 + 64, mt * 128 + cw * 64);
      asm volatile("cp.async.bulk.commit_group; cp.async.bulk.wait_group 0;" ::: "memory");
    }
  }
  __syncwarp();
  cluster_sync();
  if (tid == 0) STAMP(4);
  if (nt == 0 && mt == 0) asm volatile("griddepcontrol.wait;" ::: "memory");
}

__host__ __device__ constexpr uint32_t wpage(int L) {
  return (uint32_t)(((L & 1) << 18) | (((L >> 1) & 1) << 20) | (((L >> 2) & 1) << 13) | (((L >> 3) & 1) << 16) | (((L >> 4) & 1) << 17) |
                    (((L >> 5) & 1) << 19) | ((((L >> 2) ^ (L >> 3) ^ (L >> 4) ^ (L >> 5)) & 1) << 12));
}
constexpr int L_MEM = 0;
constexpr int L_U = 4;
constexpr int L_VM = 20;
constexpr int L_FLAG = 52;
constexpr int L_END = 53, L_PROBE = 60;
struct Rings {
  uint4 vx[4][64 * 256];
  int ctr[5][32];
};
__device__ Rings g_rings;
__device__ uint4 g_win[(4 << 20) / 16];
__device__ unsigned g_epoch;
__device__ bf16 g_ux[S_LEN * HD];

constexpr int SB0 = 1024;
constexpr int R_WS = 0;
constexpr int R_X = 65536;
constexpr int R_H1 = R_X + 32768;
constexpr int R_MEM = R_X + 131072;
constexpr int R_BARS = R_MEM + 16384;
constexpr int R_SB = R_BARS + 256;
constexpr int R_OB = R_SB + 3072;
constexpr int R_TRC = R_OB + 8192;
constexpr int R_VT = (R_TRC + 512 + 1023) & ~1023;
constexpr int R_VT2 = R_SB + 1024, R_VT3 = R_VT + 4096;
constexpr int R_SMEM = R_VT3 + 2048;
constexpr int R_QM = R_OB, R_KM = R_OB + 2048, R_VM = R_OB + 4096  , R_P = R_VT  ;
constexpr int R_XS = R_X + 98304;
constexpr int R_QX = R_XS + 8192, R_KX = R_QX + 4096, R_VX = R_KX + 4096  ;
constexpr int R_TAB = R_VX + 8192;
constexpr int B_RES = 64, B_PAIR = 72, B_XS = 80, B_H0 = 88, B_H1 = 96  , B_XF = 96  ;

#define POLL_LIMIT (1 << 18)
#define TR(i)
#define TRD()
#define TRB(i)

#define LOOK0 0
#define LOOK1 1
#define VLOOK 32
#define VN 4
#define VP2 33
#define ULOOK 0
#define XV 1
#define WDLY 100
#define W3 1
#define VB 16
#define VPRE 1
#define WDL2 100
#define USTAG 60
#define NPRE 3
#define XP 4
#define PART 1
#define DP 0
template <bool B> struct BoolC { static constexpr bool value = B; };
template <int N> struct IntC { static constexpr int value = N; };
template <typename T> __device__ __forceinline__ T* goff(T* base, uint32_t bytes) {
  return reinterpret_cast<T*>(reinterpret_cast<char*>(base) + bytes);
}
__device__ __forceinline__ void ld_relaxed16_if(uint4& v, const void* p, uint32_t cond) {
  asm volatile("{.reg .pred q; setp.ne.u32 q, %5, 0; @q ld.relaxed.gpu.global.v4.u32 {%0,%1,%2,%3}, [%4];}"
               : "+r"(v.x), "+r"(v.y), "+r"(v.z), "+r"(v.w) : "l"(p), "r"(cond) : "memory");
}
__device__ __forceinline__ constexpr int mem_off(int i) { return (i & 1) * 2048 + (i >> 1) * (1 << 18); }
__device__ __forceinline__ bool any_empty(const uint4* v) {
  return __any_sync(~0u, max(max(umax4(v[0]), umax4(v[1])), max(umax4(v[2]), umax4(v[3]))) == SENT);
}
__device__ __forceinline__ void poll_mem(uint4* v, const char* src) {
  if (__builtin_expect(any_empty(v), 0)) {
    int it = 0;
    do {
#pragma unroll
      for (int i = 0; i < 4; i++) ld_relaxed16_if(v[i], src + mem_off(i), umax4(v[i]) == SENT);
      if (++it > POLL_LIMIT) FAIL(2000);
    } while (any_empty(v));
  }
}
__device__ __forceinline__ uint32_t uadd(uint32_t a, uint32_t b) { uint32_t o; asm("add.u32 %0, %1, %2;" : "=r"(o) : "r"(a), "r"(b)); return o; }
__device__ __forceinline__ char* other(char* p) { return reinterpret_cast<char*>(reinterpret_cast<uintptr_t>(p) ^ 4096); }
template <int N> __device__ __forceinline__ uint32_t idle(uint32_t z) {
#pragma unroll
  for (int i = 0; i < N; i++) asm volatile("mad.lo.u32 %0, %0, %0, %0;" : "+r"(z));
  return z;
}
__device__ __forceinline__ uint32_t gtime() { uint32_t t; asm volatile("mov.u32 %0, %%globaltimer_lo;" : "=r"(t)); return t; }
__device__ __forceinline__ void spin_gt(uint32_t t) { for (int i = 0; i < 4096 && __any_sync(~0u, (int)(gtime() - t) < 0); i++) { } }
__device__ __forceinline__ uint32_t last_exchange(const char* flags, int s) {
  uint2 f;
  for (int it = 0; it < POLL_LIMIT; it++) {
    f = ld_relaxed8(flags);
    if (!__any_sync(~0u, ((f.x - s) | (f.y - s)) & 16)) break;
  }
  const uint32_t now = gtime();
  return now - __reduce_min_sync(~0u, min(now - (f.x & ~31u), now - (f.y & ~31u)));
}
__device__ __forceinline__ void spin_until(uint32_t t) { while (__any_sync(~0u, (int)(clock() - t) < 0)) { } }
__device__ __forceinline__ uint32_t junk() { uint32_t x; asm volatile("" : "=r"(x)); return x; }
__device__ __forceinline__ float rcp_fast(float x) { float y; asm("rcp.approx.ftz.f32 %0, %1;" : "=f"(y) : "f"(x)); return y; }
__device__ __forceinline__ void mma_z(float* d, uint32_t a0, uint32_t a1, uint32_t a2, uint32_t a3, uint32_t b0, uint32_t b1) {
  asm volatile("mma.sync.aligned.m16n8k16.row.col.f32.bf16.bf16.f32 {%0,%1,%2,%3}, {%4,%5,%6,%7}, {%8,%9}, {%10,%10,%10,%10};"
               : "=f"(d[0]), "=f"(d[1]), "=f"(d[2]), "=f"(d[3])
               : "r"(a0), "r"(a1), "r"(a2), "r"(a3), "r"(b0), "r"(b1), "f"(0.f));
}
__device__ __forceinline__ void mma1688z(float* d, uint32_t a0, uint32_t a1, uint32_t b0) {
  asm volatile("mma.sync.aligned.m16n8k8.row.col.f32.bf16.bf16.f32 {%0,%1,%2,%3}, {%4,%5}, {%6}, {%7,%7,%7,%7};"
               : "=f"(d[0]), "=f"(d[1]), "=f"(d[2]), "=f"(d[3]) : "r"(a0), "r"(a1), "r"(b0), "f"(0.f));
}
#define MMA_W(d, o, b0, b1) mma16816(d, w[o], w[(o) + 1], w[(o) + 2], w[(o) + 3], b0, b1)
#define MMA_X(d, x, b0, b1) mma16816(d, (x)[0], (x)[1], (x)[2], (x)[3], b0, b1)
#define MMA_XZ(d, x, b0, b1) mma_z(d, (x)[0], (x)[1], (x)[2], (x)[3], b0, b1)
__device__ __forceinline__ void ldw(uint32_t* x, uint32_t a) { ldsm4t(x[0], x[1], x[2], x[3], a); }
__device__ __forceinline__ void ldm(uint32_t* x, uint32_t a) { ldsm4(x[0], x[1], x[2], x[3], a); }
template <int I> __device__ __forceinline__ void bar_arrive_i() { asm volatile("bar.arrive %0, 256;" ::"n"(I) : "memory"); }
template <int I> __device__ __forceinline__ void bar_sync_i() { asm volatile("bar.sync %0, 256;" ::"n"(I) : "memory"); }
template <int W> __device__ __forceinline__ void share_mem(const uint4* v, uint32_t mb) {
#pragma unroll
  for (int i = 0; i < 4; i++) sts16(mb + (i * 4 + W) * 512, v[i]);
  bar_arrive_i<8 + ((W + 1) & 3)>(); bar_arrive_i<8 + ((W + 2) & 3)>(); bar_arrive_i<8 + ((W + 3) & 3)>();
}
template <bool KB, typename G0>
__device__ __forceinline__ void gemv_qk(const uint32_t* w, uint32_t mb, uint32_t ws, uint32_t ka, uint32_t zero, G0 gate, uint32_t* kb, uint32_t* x) {
  float a[4], b[4], a2[4], b2[4];
  uint32_t pp[NPRE][16];
  auto ld4 = [&](uint32_t* p, int j) __attribute__((always_inline)) {
    const uint32_t q = ws + j * 4096;
    ldw(p, q); ldw(p + 4, q + 16384); ldw(p + 8, q + 2048); ldw(p + 12, q + 16384 + 2048);
  };
#pragma unroll
  for (int j = 0; j < NPRE; j++) ld4(pp[j], j);
  gate();
#pragma unroll
  for (int j = 0; j < 4; j++) {
    uint32_t* pre = pp[j % NPRE];
    const uint4 m = lds16(mb + (12 + j) * 512);
    if (j == 0) {
      MMA_XZ(a, pre, m.x, m.y); MMA_XZ(b, pre + 4, m.x, m.y); MMA_XZ(a2, pre + 8, m.z, m.w); MMA_XZ(b2, pre + 12, m.z, m.w);
    } else {
      MMA_X(a, pre, m.x, m.y); MMA_X(b, pre + 4, m.x, m.y); MMA_X(a2, pre + 8, m.z, m.w); MMA_X(b2, pre + 12, m.z, m.w);
    }
    if (j + NPRE < 4) ld4(pre, j + NPRE);
#pragma unroll
    for (int i = 0; i < 3; i++) {
      const int o = (i * 4 + j) * 8;
      const uint4 e = lds16(mb + (i * 4 + j) * 512);
      if (KB && j == 3 && i == 1) { ka += e.x & zero; ldm(kb, ka); ldm(kb + 4, ka + 2048); }
      MMA_W(a, o, e.x, e.y); MMA_W(b, 96 + o, e.x, e.y);
      MMA_W(a2, o + 4, e.z, e.w); MMA_W(b2, 100 + o, e.z, e.w);
    }
  }
  x[0] = pack_bf16(a[0] + a2[0], a[1] + a2[1]); x[1] = pack_bf16(a[2] + a2[2], a[3] + a2[3]);
  x[2] = pack_bf16(b[0] + b2[0], b[1] + b2[1]); x[3] = pack_bf16(b[2] + b2[2], b[3] + b2[3]);
}
template <int W, typename F, typename G0>
__device__ __forceinline__ void gemv_v(const uint32_t* w, const char* src, float* a, uint32_t mb, uint32_t ws, G0 gate, F tr) {
  uint32_t pa[16], pb[16];
  auto ld4 = [&](uint32_t* p, int j) __attribute__((always_inline)) {
    const uint32_t q = ws + (j & 3) * 4096;
    ldw(p, q); ldw(p + 4, q + 2048); ldw(p + 8, q + 16384); ldw(p + 12, q + 16384 + 2048);
  };
  gate();
  uint4 v[4];
#pragma unroll
  for (int i = 0; i < 4; i++) v[i] = ld_relaxed16(src + mem_off(i));
  ld4(pa, W); ld4(pb, W + 1);
  poll_mem(v, src);
  share_mem<W>(v, mb);
  tr();
  float b[4], a2[4], b2[4];
#pragma unroll
  for (int n = 0; n < 4; n++) {
    const int j = (W + n) & 3;
    uint32_t* pre = (n & 1) ? pb : pa;
    uint4 m[4];
#pragma unroll
    for (int i = 0; i < 4; i++) m[i] = n ? lds16(mb + (i * 4 + j) * 512) : v[i];
    if (n == 0) {
      MMA_XZ(a, pre, m[2].x, m[2].y); MMA_XZ(b, pre + 4, m[2].z, m[2].w);
      MMA_XZ(a2, pre + 8, m[3].x, m[3].y); MMA_XZ(b2, pre + 12, m[3].z, m[3].w);
    } else {
      MMA_X(a, pre, m[2].x, m[2].y); MMA_X(b, pre + 4, m[2].z, m[2].w);
      MMA_X(a2, pre + 8, m[3].x, m[3].y); MMA_X(b2, pre + 12, m[3].z, m[3].w);
    }
    if (n < 2 && VPRE) ld4(pre, W + n + 2);
    const int o = 128 + j * 8;
    MMA_W(a, o, m[0].x, m[0].y); MMA_W(b, o + 4, m[0].z, m[0].w);
    MMA_W(a2, o + 32, m[1].x, m[1].y); MMA_W(b2, o + 36, m[1].z, m[1].w);
    if (n == 0) bar_sync_i<8 + W>();
  }
#pragma unroll
  for (int i = 0; i < 4; i++) a[i] = (a[i] + b[i]) + (a2[i] + b2[i]);
}
__device__ __forceinline__ uint64_t cdesc(uint32_t v, int off) {
  const uint32_t lo = v + (uint32_t)(((SB0 + off) >> 4) | (1 << 16));
  return ((uint64_t)0x40000040u << 32) | lo;
}
__device__ __forceinline__ constexpr int xk(int k) { return (k >> 2) * 4096 + (k & 3) * 32; }
__device__ __forceinline__ void issue_x(const CUtensorMap* tm, uint32_t dst, uint32_t bar, int seg, int h) {
  asm volatile("cp.async.bulk.tensor.3d.shared::cluster.global.mbarrier::complete_tx::bytes.multicast::cluster [%0], [%1, {%3, %4, %5}], [%2], %6;"
               ::"r"(dst), "l"(tm), "r"(bar), "r"(0), "r"(seg * SEG), "r"(h * 8), "h"((uint16_t)3) : "memory");
}
constexpr uint32_t ONE2 = 0x3F803F80u;
constexpr float SCL = 0.08838834764831845f * 1.4426950408889634f;
__device__ __forceinline__ void exp10v(float* sc, uint32_t* p) {
  float ml = fmaxf(fmaxf(fmaxf(sc[0], sc[1]), fmaxf(sc[2], sc[3])), fmaxf(fmaxf(sc[4], sc[5]), fmaxf(sc[6], sc[7])));
  ml = fmaxf(ml, fmaxf(sc[8], sc[9]));
  const float m1 = __shfl_xor_sync(~0u, ml, 1), m2 = __shfl_xor_sync(~0u, ml, 2), m3 = __shfl_xor_sync(~0u, ml, 3);
  const float mo = fmaxf(fmaxf(ml, m1), fmaxf(m2, m3)) * SCL;
#pragma unroll
  for (int i = 0; i < 5; i++) p[i] = pack_bf16(ex2(fmaf(sc[2 * i], SCL, -mo)), ex2(fmaf(sc[2 * i + 1], SCL, -mo)));
}
__device__ __forceinline__ void gemv_o(const uint32_t* w, const char* src, uint32_t owr) {
  uint4 uv[8];
#pragma unroll
  for (int q = 0; q < 8; q++) uv[q] = ld_relaxed16(src + q * 512);
  auto pass = [&]() __attribute__((always_inline)) {
    float a0[4], a1[4], a2[4], a3[4];
#pragma unroll
    for (int i = 0; i < 8; i++) {
      const int o = i * 16;
      if (i == 0) {
        MMA_XZ(a0, w, uv[0].x, uv[0].y); MMA_XZ(a1, w + 4, uv[0].x, uv[0].y); MMA_XZ(a2, w + 8, uv[0].z, uv[0].w); MMA_XZ(a3, w + 12, uv[0].z, uv[0].w);
      } else {
        MMA_W(a0, o, uv[i].x, uv[i].y); MMA_W(a1, o + 4, uv[i].x, uv[i].y); MMA_W(a2, o + 8, uv[i].z, uv[i].w); MMA_W(a3, o + 12, uv[i].z, uv[i].w);
      }
    }
    const float x = a0[0] + a2[0], y = a0[1] + a2[1];
    sts16f(owr, x, a0[2] + a2[2], y, a0[3] + a2[3]);
    sts16f((owr ^ 32) + 512, a1[0] + a3[0], a1[2] + a3[2], a1[1] + a3[1], a1[3] + a3[3]);
    return x + y;
  };
  const float t = pass();
  if (__builtin_expect(__any_sync(~0u, t != t), 0)) {
    for (int it = 0;; it++) {
      uint32_t m = 0;
#pragma unroll
      for (int i = 0; i < 8; i++) {
        const uint32_t mi = umax4(uv[i]);
        m = max(m, mi);
        ld_relaxed16_if(uv[i], src + i * 512, mi == SENT);
      }
      if (!__any_sync(~0u, m == SENT)) break;
      if (it > POLL_LIMIT) FAIL(4000);
    }
    pass();
  }
}

__global__ void __launch_bounds__(256, 1)
rec_kernel(const __grid_constant__ CUtensorMap tmWq, const __grid_constant__ CUtensorMap tmWk,
           const __grid_constant__ CUtensorMap tmWv, const __grid_constant__ CUtensorMap tmWo,
           const __grid_constant__ CUtensorMap tmX, const bf16* __restrict__ mem0, const bf16* __restrict__ xin,
           char* __restrict__ G, int d_u, int d_m, int d_q, int zero) {
  extern __shared__ __align__(1024) uint8_t smem_raw[];
  const uint32_t sb = smem_u32(smem_raw);
  if ((sb & 0x3FFFF) != SB0) __trap();
  if (threadIdx.x == 0) STAMP(0);
  for (int i = blockIdx.x * 256 + threadIdx.x; i < (int)(sizeof(Rings) / 16); i += 128 * 256)
    reinterpret_cast<uint4*>(&g_rings)[i] = make_uint4(~0u, ~0u, ~0u, ~0u);
  for (int i = blockIdx.x; i < L_END * 8; i += 128)
    *reinterpret_cast<uint4*>(G + (wpage(i >> 3) ^ ((i & 1) << 12)) + ((i >> 1) & 3) * 16384 + threadIdx.x * 16) = make_uint4(~0u, ~0u, ~0u, ~0u);
  const int tid = threadIdx.x, t7 = tid & 127, lane = tid & 31;
#define UNI(x) __reduce_max_sync(~0u, (uint32_t)(x))
#define OPQ(x) __shfl_sync(~0u, (uint32_t)(x), lane)
  const int warp = UNI(tid >> 5), wg = warp >> 2, w4 = warp & 3;
  const int bid = UNI(blockIdx.x);
  const int r = bid & 1, cl = bid >> 1, head = cl >> 1;
  const bool is_qk = (cl & 1) == 0;
  const uint32_t bars = sb + R_BARS;
  if (tid == 0) {
    for (int i = 0; i < 16; i++) mbar_init(bars + i * 8, (i * 8 == B_XS) ? 4 : 1);
    asm volatile("fence.mbarrier_init.release.cluster;" ::: "memory");
  }
  __syncthreads();
  const int cta = head * 2 + r, fcol = cta * 64;
  const uint32_t stg = sb + R_X + wg * 65536;
  const uint32_t sbar = bars + wg * 32;
  const int lk = (lane & 7) + ((lane >> 4) << 3);
  const uint32_t wt_off = lk * 128 + (((w4 * 2 + ((lane >> 3) & 1)) ^ (lk & 7)) << 4);
  const int g = lane >> 2, c = lane & 3;
  if (tid == 32 && bid < XP)
    asm volatile("cp.async.bulk.prefetch.L2.global [%0], 32768;" ::"l"(xin + (size_t)bid * 16384) : "memory");
  if (tid == 64) {
    __threadfence();
    const unsigned target = (atomicAdd(&g_epoch, 1u) & ~127u) + 128u;
    asm volatile("griddepcontrol.launch_dependents;" ::: "memory");
    for (int i = 0; i < (1 << 22); i++) {
      unsigned v; asm volatile("ld.acquire.gpu.global.u32 %0, [%1];" : "=r"(v) : "l"(&g_epoch) : "memory");
      if ((int)(v - target) >= 0) break;
    }
  }
  if (tid == 96) {
    unsigned* p0 = reinterpret_cast<unsigned*>(G + wpage(L_PROBE) + (bid >> 5) * 16384 + (bid & 31) * 128);
    unsigned best[2] = {~0u, ~0u}, x = 0;
    for (int i = 0; i < 12; i++) {
      const unsigned t0 = clock();
      x = atomicExch(p0 + (i & 1) * 1024 + (x >> 31), (unsigned)i);
      const unsigned t1 = clock() + (x >> 31);
      best[i & 1] = min(best[i & 1], t1 - t0);
    }
    sts4f(sb + R_SB, __uint_as_float(PART && best[1] < best[0] ? 4096u : 0u));
  }
  __syncwarp();
  uint32_t w[192];
  const uint32_t t16_ = OPQ(sb + tid * 16);
#define BASES() uint32_t t16 = t16_; keep32(t16); const uint32_t l16 = t16 - warp * 512; (void)l16
  const uint32_t ws0 = sb + R_WS + wg * 32768 + wt_off;

  if (is_qk) {
    const CUtensorMap* tmA = wg ? &tmWq : &tmWk;
    const CUtensorMap* tmB = wg ? &tmWk : &tmWq;
    if (t7 == 0) {
      for (int i = 0; i < 4; i++) {
        mbar_expect_tx(sbar + i * 8, 16384);
        tma2d_ef(stg + i * 16384, i < 3 ? tmA : tmB, fcol, wg * 512 + (i % 3) * 128, sbar + i * 8);
      }
      if (wg == 0) {
        mbar_expect_tx(bars + B_RES, 65536);
        for (int i = 0; i < 4; i++)
          tma2d_ef(sb + R_WS + i * 16384, (i == 0 || i == 3) ? &tmWk : &tmWq, fcol, (i >> 1) * 512 + 384, bars + B_RES);
      }
    }
#pragma unroll
    for (int i = 0; i < 6; i++) {
      mbar_wait(sbar + (i & 3) * 8, i >> 2);
#pragma unroll
      for (int j = 0; j < 8; j++) {
        const int o = (i * 8 + j) * 4;
        ldsm4t(w[o], w[o + 1], w[o + 2], w[o + 3], stg + (i & 3) * 16384 + j * 2048 + wt_off);
      }
      if (i == 1) {
        bar_sync(1 + wg, 128);
        if (t7 == 0)
          for (int i2 = 4; i2 < 6; i2++) {
            mbar_expect_tx(sbar + (i2 & 3) * 8, 16384);
            tma2d_ef(stg + (i2 & 3) * 16384, tmB, fcol, wg * 512 + (i2 - 3) * 128, sbar + (i2 & 3) * 8);
          }
      }
    }
    mbar_wait(bars + B_RES, 0);
    if (tid == 32 && bid >= XP) asm volatile("cp.async.bulk.prefetch.L2.global [%0], 32768;" ::"l"(xin + (size_t)bid * 16384) : "memory");
    cluster_sync();
    if (threadIdx.x == 0) STAMP(1);
    if (tid == 224) {
      mbar_expect_tx(bars + B_H0, 32768); mbar_expect_tx(bars + B_H1, 32768); mbar_expect_tx(bars + B_H1 + 8, 32768);
      if (r) { issue_x(&tmX, sb + R_H1, bars + B_H1, 0, 1); issue_x(&tmX, sb + R_H1 + 32768, bars + B_H1 + 8, 1, 1); }
      else issue_x(&tmX, sb + R_X, bars + B_H0, 0, 0);
      mbar_expect_tx(bars + B_PAIR, 1536);
    }
    const uint32_t near = UNI(__float_as_uint(lds4f(sb + R_SB)));
    __syncthreads();
    const uint32_t rdelta = UNI(mapa(sb, r ^ 1) - sb);
    const uint32_t sbo = UNI(R_SB + (w4 & 1) * 8 + (wg ? 1024 : (w4 >> 1) * 512));
    const uint32_t sbr = UNI(rdelta + (sb >> 1) + R_SB + 1536 + (wg ? 4 + (w4 & 1) : w4) * 256);
    {
      const int ch = 2 * w4 + ((lane >> 3) & 1);
      const uint32_t qst = sb + (lane & 7) * 16 + (((lane >> 4) ^ wg) ? R_QM + ch * 256 + wg * 128 : R_KM + wg * 1024 + ch * 128);
      const uint32_t fst = sb + (lane & 7) * 16 + R_QX + (lane >> 4) * 128 + ch * 256;
      const uint32_t fstk = sb + (lane & 7) * 16 + R_KX + (ch >> 2) * 2048 + (lane >> 4) * 512 + (ch & 3) * 128;
      const uint32_t gu = wpage(L_U + (cta >> 2)) + (cta & 3) * 1024;
      sts16(t16_ + R_TAB, make_uint4(near + t7 * 16, fst, ws0, qst));
      sts16(t16_ + R_TAB + 4096, make_uint4((wpage(L_VM + head) ^ near) + r * 2048 + t7 * 8,
                                            wg ? gu + (w4 >> 1) * 512 + lane * 16 : gu + (w4 >> 1) * 512 + g * 64 + (w4 & 1) * 32 + c * 8, fstk, (wpage(L_FLAG) ^ near) + lane * 8));
    }
    auto finish = [&](float* d, const float4* p, uint32_t fst, int f2) __attribute__((always_inline)) {
      acc_fence16(d);
      uint32_t f[8];
#pragma unroll
      for (int i = 0; i < 4; i++) {
        f[2 * i] = pack_bf16(d[4 * i] + p[i].x, d[4 * i + 1] + p[i].y);
        f[2 * i + 1] = pack_bf16(d[4 * i + 2] + p[i].z, d[4 * i + 3] + p[i].w);
      }
      stsm4t(fst, f[0], f[1], f[2], f[3]);
      stsm4t(fst + f2, f[4], f[5], f[6], f[7]);
    };
    auto proj0 = [&](int s, auto mid) __attribute__((always_inline)) {
      float da[16], db[16];
      const uint32_t z = ((s + 1) & 1) * 2048;
      WG_FENCE();
#pragma unroll
      for (int j = 0; j < 8; j++) {
        if (j == 0) { wg_ss32z(da, cdesc(0, R_WS + 49152), cdesc(z, R_H1 + xk(24))); wg_ss32z(db, cdesc(0, R_WS + 32768), cdesc(z, R_H1 + xk(24))); }
        else {
          wg_ss32(da, cdesc(0, R_WS + 49152 + j * 2048), cdesc(z, R_H1 + xk(24 + j)));
          wg_ss32(db, cdesc(0, R_WS + 32768 + j * 2048), cdesc(z, R_H1 + xk(24 + j)));
        }
      }
      WG_COMMIT();
      TR(8);
      mbar_wait(bars + B_H0, (s + 1) & 1);
      TR(9);
      WG_FENCE();
#pragma unroll
      for (int j = 0; j < 8; j++) {
        wg_ss32(da, cdesc(0, R_WS + j * 2048), cdesc(0, R_X + xk(24 + j)));
        wg_ss32(db, cdesc(0, R_WS + 16384 + j * 2048), cdesc(0, R_X + xk(24 + j)));
      }
#pragma unroll
      for (int k = 0; k < 24; k++) wg_rs32<1>(da, w + 4 * k, cdesc(0, R_X + xk(k)));
      WG_COMMIT();
#pragma unroll
      for (int k = 0; k < 24; k++) wg_rs32<1>(db, w + 96 + 4 * k, cdesc(0, R_X + xk(k)));
      WG_COMMIT();
      mid();
      bar_sync(5, 256);
      float4 p[4];
#pragma unroll
      for (int i = 0; i < 4; i++) p[i] = lds16f(t16_ + (R_H1 + 8192) + z * 16 + i * 2048);
      const uint32_t fst = lds4(t16_ + R_TAB + 4), fstk = lds4(t16_ + R_TAB + 4104);
      WG_WAIT(1);
      TR(10);
      finish(da, p, fstk, 1024);
#pragma unroll
      for (int i = 0; i < 4; i++) p[i] = lds16f(t16_ + R_H1 + z * 16 + i * 2048);
      WG_WAIT(0);
      TR(11);
      finish(db, p, fst, 2048);
    };
    auto pv_seg = [&](int s) __attribute__((always_inline)) {
      BASES();
      uint32_t p[12];
      const uint32_t pa = l16 + R_P + (w4 >> 1) * 256 + (t16 & 256);
      ldm(p, pa); ldm(p + 4, pa + 1024); ldm(p + 8, (pa & ~512u) + 2048);
      const uint32_t vb = l16 + (w4 & 1) * 1024 + (t16 & 256) - (t16 & 128);
      const uint32_t vx = vb + R_VX + (s & 1) * 4096 + (t16 & 128) * 16, vm = vb + R_VM + (s & 1) * 2048 + ((t16 >> 4) & 8);
      float d[4][4];
#pragma unroll
      for (int t = 0; t < 4; t++) {
        const uint4 x = lds16(vx + t * 128);
        const uint2 m = lds8(vm + t * 128);
        MMA_XZ(d[t], p, x.x, x.y); MMA_X(d[t], p + 4, x.z, x.w); MMA_X(d[t], p + 8, m.x, m.y);
      }
      float os[4];
      MMA_XZ(os, p, ONE2, ONE2); MMA_X(os, p + 4, ONE2, ONE2); mma1688(os, p[8], p[9], ONE2);
      const float i0 = rcp_fast(os[0]), i1 = rcp_fast(os[2]);
      uint4* dst = goff(reinterpret_cast<uint4*>(g_ux + (size_t)(s * SEG + (w4 >> 1) * 16) * HD + fcol + (w4 & 1) * 32), (t16 & 448) * (HD / 32) + (t16 & 48));
      dst[0] = make_uint4(pack_bf16(d[0][0] * i0, d[0][1] * i0), pack_bf16(d[1][0] * i0, d[1][1] * i0),
                          pack_bf16(d[2][0] * i0, d[2][1] * i0), pack_bf16(d[3][0] * i0, d[3][1] * i0));
      dst[HD] = make_uint4(pack_bf16(d[0][2] * i1, d[0][3] * i1), pack_bf16(d[1][2] * i1, d[1][3] * i1),
                           pack_bf16(d[2][2] * i1, d[2][3] * i1), pack_bf16(d[3][2] * i1, d[3][3] * i1));
    };
    auto soft = [&](int s, int q) __attribute__((always_inline)) {
      BASES();
      mbar_wait(bars + B_XS, s & 1);
      TR(2);
      float sc[10];
      {
        const float4 p0 = lds16f(l16 + R_XS + q * 512), p1 = lds16f(l16 + R_XS + 4096 + q * 512);
        const float4 q0 = lds16f(l16 + R_XS + 2048 + (q & 1) * 512), q1 = lds16f(l16 + R_XS + 6144 + (q & 1) * 512);
        const float2 m0 = lds8f(l16 + R_XS + 3072 + (q >> 1) * 512 + (q & 1) * 8), m1 = lds8f(l16 + R_XS + 7168 + (q >> 1) * 512 + (q & 1) * 8);
        sc[0] = p0.x + p1.x; sc[1] = p0.y + p1.y; sc[2] = p0.z + p1.z; sc[3] = p0.w + p1.w;
        sc[4] = q0.x + q1.x; sc[5] = q0.y + q1.y; sc[6] = q0.z + q1.z; sc[7] = q0.w + q1.w;
        sc[8] = m0.x + m1.x; sc[9] = m0.y + m1.y;
        const int dlt = q * 8 + (int)((t16 >> 6) & 7) - (int)((t16 >> 3) & 6);
#pragma unroll
        for (int i = 0; i < 8; i++) sc[i] = dlt >= (i >> 1) * 8 + (i & 1) ? sc[i] : -INFINITY;
      }
      {
        uint32_t p[5];
        exp10v(sc, p);
        const uint32_t pa = l16 + R_P + q * 128 + (t16 & 384) * 3;
        stsm4(pa, p[0], p[1], p[2], p[3]);
        stsm1(l16 + R_P + 2048 + q * 128, p[4]);
      }
      TR(6);
    };
    auto proj1 = [&](int s) __attribute__((always_inline)) {
      float da[16], db[16];
      const uint32_t z = ((s + 1) & 1) * 2048;
      uint32_t rb0 = SENT, rb1 = SENT;
      if (w4 == 0) {
        char* urs = G + (lds4(t16_ + R_TAB + 4100) + (((s + 2) & 3) << 14));
        char* urs2 = other(urs);
        const uint4 e = make_uint4(SENT, SENT, SENT, SENT);
        st_relaxed16(urs, e); st_relaxed16(urs + 512, e); st_relaxed16(urs2, e); st_relaxed16(urs2 + 512, e);
        rb0 = ld_relaxed4(urs + 512); rb1 = ld_relaxed4(urs2 + 512);
      }
      WG_FENCE();
#pragma unroll
      for (int k = 0; k < 24; k++) {
        if (k == 0) { wg_rs32<0>(da, w, cdesc(z, R_H1)); wg_rs32<0>(db, w + 96, cdesc(z, R_H1)); }
        else { wg_rs32<1>(da, w + 4 * k, cdesc(z, R_H1 + xk(k))); wg_rs32<1>(db, w + 96 + 4 * k, cdesc(z, R_H1 + xk(k))); }
      }
      WG_COMMIT();
      TR(8);
      if (s >= 0) {
        if (t16_ == sb + 160 * 16 && s + 2 < NSEG) {
          mbar_expect_tx(bars + B_H1 + (s & 1) * 8, 32768);
          if (r) issue_x(&tmX, sb + R_H1 + (s & 1) * 32768, bars + B_H1 + (s & 1) * 8, s + 2, 1);
        }
        __syncwarp();
      }
      if (w4 & 1) {
        BASES();
        const uint32_t o = (t16 - sb - 2560) & ~512u;
        const char* vxp = reinterpret_cast<const char*>(g_rings.vx[(s + 1) & 3] + cta * 256) + o;
        uint4 x[4];
#pragma unroll
        for (int i = 0; i < 4; i++) x[i] = ld_relaxed16(vxp + (i & 1) * 512 + (i >> 1) * 2048);
        for (int it = 0; __builtin_expect(any_empty(x), 0); it++) {
#pragma unroll
          for (int i = 0; i < 4; i++) x[i] = ld_relaxed16(vxp + (i & 1) * 512 + (i >> 1) * 2048);
          if (it > POLL_LIMIT) FAIL(5000 + s);
        }
#pragma unroll
        for (int i = 0; i < 4; i++) sts16(sb + o + R_VX + ((s + 1) & 1) * 4096 + (i & 1) * 512 + (i >> 1) * 2048, x[i]);
        if (w4 == 3 && s >= 0) sts4f(sb + R_BARS + 128, __uint_as_float(last_exchange(G + lds4(t16 + R_TAB + 4108), s) + d_q));
      } else if (w4 == 0) {
        keep32(rb0); keep32(rb1);
        if (__any_sync(~0u, (rb0 & rb1) != SENT)) FAIL(6000);
      } else if (s >= 0) soft(s, 0);
      TR(9);
      WG_WAIT(0);
      acc_fence16(da); acc_fence16(db);
      TR(10);
#pragma unroll
      for (int i = 0; i < 4; i++) {
        sts16f(t16_ + (R_H1 + 6144) + z * 16 + i * 2048, db[4 * i], db[4 * i + 1], db[4 * i + 2], db[4 * i + 3]);
        sts16f(t16_ + (R_H1 - 2048) + z * 16 + i * 2048, da[4 * i], da[4 * i + 1], da[4 * i + 2], da[4 * i + 3]);
      }
      bar_arrive(5, 256);
      const char* src = G + (lds4(t16_ + R_TAB) + (((s + 1) & 3) << 14));
      if (s >= 0) { bar_sync(10, 128); spin_gt(lds4(sb + R_BARS + 128)); }
      TR(12);
      uint4 v[8];
#pragma unroll
      for (int i = 0; i < 8; i++) v[i] = ld_relaxed16(src + mem_off(i & 3) + (i >> 2) * (1 << 20));
      for (int it = 0; any_empty(v) || any_empty(v + 4); it++) {
#pragma unroll
        for (int i = 0; i < 8; i++) ld_relaxed16_if(v[i], src + mem_off(i & 3) + (i >> 2) * (1 << 20), umax4(v[i]) == SENT);
        if (it > POLL_LIMIT) FAIL(2000);
      }
#pragma unroll
      for (int i = 0; i < 8; i++) sts16(t16_ + (R_MEM - 2048) + i * 2048, v[i]);
      bar_arrive(7, 256);
    };
    mbar_wait(bars + B_H1, 0);
    if (wg == 0) proj0(-1, []() {}); else proj1(-1);
    auto step = [&](int s, auto last_c) __attribute__((always_inline)) {
      constexpr bool last = decltype(last_c)::value;
      uint2 tb;
      {
        BASES();
        const uint2 ta = lds8(t16 + R_TAB + 8);
        uint32_t kb[8], x[4];
        gemv_qk<!last>(w, l16 + R_MEM + wg * 8192, ta.x, t16 + R_KX, zero, [&]() __attribute__((always_inline)) {
          TR(14);
          bar_sync(7 + wg, 256 >> wg);
          TRB(0);
        }, kb, x);
        stsm4t(ta.y, x[0], x[1], x[2], x[3]);
        TR(1);
        bar_sync(0, 256);
        auto seg_w = [&](auto wc, uint32_t l) __attribute__((always_inline)) {
          constexpr int W = decltype(wc)::value;
          auto seg = [&](uint32_t l) __attribute__((always_inline)) {
            float xm[4], xt[4], s0[4], s1[4];
#pragma unroll
            for (int i = 0; i < 2; i++) {
              uint32_t a0[4], a1[4], k0[4], k1[4];
              ldm(a0, l + R_QX + (W >> 1) * 2048 + i * 1024); ldm(a1, l + R_QX + (W >> 1) * 2048 + i * 1024 + 512);
              if (W == 1 || W == 2) {
                ldm(k0, l + R_KM + i * 512); ldm(k1, l + R_KM + 1024 + i * 512);
                if (i == 0) { MMA_XZ(xm, a0, k0[0], k0[1]); MMA_XZ(xt, a0, k1[0], k1[1]); }
                else { MMA_X(xm, a0, k0[0], k0[1]); MMA_X(xt, a0, k1[0], k1[1]); }
                MMA_X(xm, a1, k0[2], k0[3]); MMA_X(xt, a1, k1[2], k1[3]);
              }
              if (W != 1) {
                ldm(k0, l + R_KX + (W == 3 ? 1024 : 0) + i * 2048); ldm(k1, l + R_KX + (W == 3 ? 1024 : 0) + 512 + i * 2048);
                if (i == 0) { MMA_XZ(s0, a0, k0[0], k0[1]); MMA_XZ(s1, a0, k1[0], k1[1]); }
                else { MMA_X(s0, a0, k0[0], k0[1]); MMA_X(s1, a0, k1[0], k1[1]); }
                MMA_X(s0, a1, k0[2], k0[3]); MMA_X(s1, a1, k1[2], k1[3]);
              }
            }
            uint32_t xo = l + R_XS + r * 4096;
            constexpr int OM = 3072 + (W >> 1) * 512, OX = (W ? W - 1 : 0) * 1024;
            float e1[4] = {s0[0], s0[1], s1[0], s1[1]}, e2[4] = {s0[2], s0[3], s1[2], s1[3]};
            if (W == 1 || W == 2) {
#pragma unroll
              for (int i = 0; i < 4; i++) xm[i] += xt[i];
              sts16f(xo + OM, xm[0], xm[1], xm[2], xm[3]);
            }
            if (W != 1) { sts16f(xo + OX, e1[0], e1[1], e1[2], e1[3]); sts16f(xo + OX + 512, e2[0], e2[1], e2[2], e2[3]); }
            TR(2);
            if (last) cluster_sync(); else mbar_wait(bars + B_PAIR, s & 1);
            if (W == 1) {
              if (!last && (t16 & 0x1F0) == 0) {
                mbar_expect_tx(bars + B_PAIR, 1536);
                mbar_expect_tx(bars + B_H0, 32768);
                if (r == 0) issue_x(&tmX, sb + R_X, bars + B_H0, s + 1, 0);
              }
              __syncwarp();
            } else xo += idle<WDL2 / 5>(t16 & zero);
            TR(3);
            const uint32_t xb = bars + B_XS + rdelta;
            if (W == 1 || W == 2) st_async16(xo + rdelta + OM, xm, xb);
            if (W != 1) { st_async16(xo + rdelta + OX, e1, xb); st_async16(xo + rdelta + OX + 512, e2, xb); }
            __syncwarp();
            mbar_arrive_tx_if(bars + B_XS, 1024, (t16 & 0x1F0) == 0);
            __syncwarp();
          };
          seg(l);
        };
        const bool xo = wg && (w4 == 1 || w4 == 2);
        if (!last && !xo) {
          if (wg) {
            ldm(kb, l16 + R_KM + (w4 & 1) * 1024);
            ldm(kb + 4, l16 + R_KM + (w4 & 1) * 1024 + 512);
          }
          float sp[4][4];
#pragma unroll
          for (int i = 0; i < 4; i++) {
            uint32_t a[4];
            ldm(a, l16 + R_QM + i * 512);
            MMA_XZ(sp[i], a, kb[2 * i], kb[2 * i + 1]);
          }
          const float x = ((sp[0][0] + sp[0][2]) + (sp[1][0] + sp[1][2])) + ((sp[2][0] + sp[2][2]) + (sp[3][0] + sp[3][2]));
          const float y = ((sp[0][1] + sp[0][3]) + (sp[1][1] + sp[1][3])) + ((sp[2][1] + sp[2][3]) + (sp[3][1] + sp[3][3]));
          st_async8((l16 >> 1) + sbr, x, y, bars + B_PAIR + rdelta);
          sts8f(l16 + sbo, x, y);
          if (wg) bar_arrive(9, 192);
        }
        if (wg) {
          switch (w4) {
            case 0: seg_w(IntC<0>(), l16); break;
            case 1:
              if (!last) st_relaxed4_if(G + (wpage(L_FLAG) ^ ((t16 & 16) << 8)) + cta * 4, (gtime() & ~31u) | (s & 31), (t16 & 0x1E0) == 0);
              seg_w(IntC<1>(), l16 + idle<WDLY / 5>(t16 & zero));
              break;
            case 2: seg_w(IntC<2>(), l16 + idle<WDLY / 5>(t16 & zero)); break;
            default: seg_w(IntC<3>(), l16); break;
          }
        }
      }
      BASES();
      if (wg == 0) {
        tb = lds8(t16 + R_TAB + 4096);
        const char* vmp = G + (tb.x + ((s & 3) << 14));
        if (last) {
          uint2 va, vb;
          int it = 0;
          do {
            va = ld_relaxed8(vmp); vb = ld_relaxed8(vmp + 1024);
            if (++it > POLL_LIMIT) FAIL(3100);
          } while (__any_sync(~0u, max(max(va.x, va.y), max(vb.x, vb.y)) == SENT));
          sts16(t16 + R_VM + (s & 1) * 2048, make_uint4(va.x, vb.x, va.y, vb.y));
          cluster_sync();
          soft(s, w4);
          bar_arrive(2, 256);
          return;
        }
        TR(3);
        uint2 va = ld_relaxed8(vmp), vb = ld_relaxed8(vmp + 1024);
        const uint4 v0 = lds16(t16 + R_VX + (s & 1) * 4096), v1 = lds16(t16 + R_VX + 2048 + (s & 1) * 4096);
        char* up = G + (tb.y + ((s & 3) << 14));
        keep64(up);
        mbar_wait(bars + B_H1 + ((s + 1) & 1) * 8, ((s + 1) >> 1) & 1);
        bar_sync(9, 192);
        const float4 p0 = lds16f(l16 + R_SB), p1 = lds16f(l16 + R_SB + 512), p2 = lds16f(l16 + R_SB + 1024);
        mbar_wait(bars + B_PAIR, s & 1);
        TR(4);
        float sc[10];
        {
          const uint32_t l8 = (l16 >> 1) + (sb >> 1) + R_SB + 1536;
          const float2 q0 = lds8f(l8), q1 = lds8f(l8 + 256), q2 = lds8f(l8 + 512), q3 = lds8f(l8 + 768), q4 = lds8f(l8 + 1024), q5 = lds8f(l8 + 1280);
          sc[0] = p0.x + q0.x; sc[1] = p0.y + q0.y; sc[2] = p0.z + q1.x; sc[3] = p0.w + q1.y;
          sc[4] = p1.x + q2.x; sc[5] = p1.y + q2.y; sc[6] = p1.z + q3.x; sc[7] = p1.w + q3.y;
          sc[8] = (p2.x + p2.z) + (q4.x + q5.x); sc[9] = (p2.y + p2.w) + (q4.y + q5.y);
        }
        uint32_t p[5];
        exp10v(sc, p);
        float o0[4], o1[4], os[4], m0[4], m1[4];
        {
          const uint32_t j0 = junk(), j1 = junk();
          mma_z(os, p[0], j0, p[1], j1, ONE2, ONE2); mma_z(o0, p[0], j0, p[1], j1, v0.x, v0.y); mma_z(o1, p[0], j0, p[1], j1, v1.x, v1.y);
        }
        const uint32_t j2 = junk();
        {
          float ot[4];
          const uint32_t j0 = junk(), j1 = junk();
          mma_z(ot, p[2], j0, p[3], j1, ONE2, ONE2);
          mma1688(os, p[4], j2, ONE2);
          mma16816(o0, p[2], j0, p[3], j1, v0.z, v0.w); mma16816(o1, p[2], j0, p[3], j1, v1.z, v1.w);
          os[0] += ot[0];
        }
        auto pvm = [&]() __attribute__((always_inline)) {
          mma1688z(m0, p[4], j2, va.x); mma1688z(m1, p[4], j2, va.y);
          mma1688(m0, p[4], j2, vb.x); mma1688(m1, p[4], j2, vb.y);
        };
        pvm();
        TR(5);
        if (__builtin_expect(__any_sync(~0u, max(max(va.x, va.y), max(vb.x, vb.y)) == SENT), 0)) {
          int it = 0;
          do {
            va = ld_relaxed8(vmp); vb = ld_relaxed8(vmp + 1024);
            if (++it > POLL_LIMIT) FAIL(3000 + s);
          } while (__any_sync(~0u, max(max(va.x, va.y), max(vb.x, vb.y)) == SENT));
          pvm();
        }
        const float inv = rcp_fast(os[0]);
        const uint32_t u0 = pack_bf16((o0[0] + m0[0]) * inv, (o0[1] + m0[1]) * inv), u1 = pack_bf16((o1[0] + m1[0]) * inv, (o1[1] + m1[1]) * inv);
        st_relaxed8(up, u0, u1);
        st_relaxed8(other(up), u0, u1);
        bar_arrive(3, 256);
        sts16(t16 + R_VM + (s & 1) * 2048, make_uint4(va.x, vb.x, va.y, vb.y));
        TR(7);
        if (W3) bar_sync(4, 256);
        proj0(s, [&]() __attribute__((always_inline)) { if (w4) soft(s, w4); });
      } else {
        if (s > 0) pv_seg(s - 1);
        if (W3 && !last) bar_arrive(4, 256);
        if (last) {
          bar_sync(2, 256);
          pv_seg(s);
          __syncwarp();
          if (lane == 0) { __threadfence(); atomicAdd(&g_rings.ctr[3][0], 1); }
          return;
        }
        TR(6);
        bar_sync(3, 256);
        TRB(7);
        proj1(s);
      }
    };
#pragma unroll 1
    for (int s = 0; s < NSEG - 1; s++) { step(s, BoolC<false>()); TRD(); }
    step(NSEG - 1, BoolC<true>());
  } else {
    if (t7 == 0) {
      for (int i = 0; i < 4; i++) {
        mbar_expect_tx(sbar + i * 8, 16384);
        tma2d(stg + i * 16384, &tmWo, head * 32, r * 2048 + (wg * 4 + i) * 256, sbar + i * 8);
      }
      if (wg == 0) {
        mbar_expect_tx(bars + B_RES, 65536);
        for (int i = 0; i < 4; i++)
          tma2d_ef(sb + R_WS + i * 16384, &tmWv, fcol, (i >> 1) * 512 + 256 + (i & 1) * 128, bars + B_RES);
      }
    }
    mbar_wait(sbar + w4 * 8, 0);
    {
      const int rr = lane & 7, mi = lane >> 3, cc = rr >> 1;
      const uint32_t a = stg + w4 * 16384 + ((cc >> 1) * 16 + (cc & 1) * 4 + (mi >> 1) * 8 + (rr & 1)) * 64 + (mi & 1) * 16;
      const int sl0 = ((2 * g) & 7) * 4 + c;
#pragma unroll
      for (int j = 0; j < 16; j++)
#pragma unroll
        for (int t = 0; t < 2; t++) {
          uint32_t x0, x1, x2, x3;
          ldsm4t(x0, x1, x2, x3, a + ((j >> 1) * 32 + (j & 1) * 2) * 64 + t * 32);
          const uint32_t e0 = __shfl_sync(~0u, x0, sl0), e1 = __shfl_sync(~0u, x1, sl0);
          const uint32_t q0 = __shfl_sync(~0u, x0, sl0 + 4), q1 = __shfl_sync(~0u, x1, sl0 + 4);
          const uint32_t e2 = __shfl_sync(~0u, x2, sl0), e3 = __shfl_sync(~0u, x3, sl0);
          const uint32_t q2 = __shfl_sync(~0u, x2, sl0 + 4), q3 = __shfl_sync(~0u, x3, sl0 + 4);
          const int o = (j * 2 + t) * 4;
          w[o] = g < 4 ? e0 : e1; w[o + 1] = g < 4 ? q0 : q1; w[o + 2] = g < 4 ? e2 : e3; w[o + 3] = g < 4 ? q2 : q3;
        }
    }
    bar_sync(1 + wg, 128);
    if (t7 == 0)
      for (int i = 0; i < 2; i++) {
        mbar_expect_tx(sbar + i * 8, 16384);
        tma2d_ef(stg + i * 16384, &tmWv, fcol, wg * 512 + i * 128, sbar + i * 8);
      }
#pragma unroll
    for (int i = 0; i < 2; i++) {
      mbar_wait(sbar + i * 8, 1);
#pragma unroll
      for (int j = 0; j < 8; j++) {
        const int o = 128 + (i * 8 + j) * 4;
        ldsm4t(w[o], w[o + 1], w[o + 2], w[o + 3], stg + i * 16384 + j * 2048 + wt_off);
      }
    }
    mbar_wait(bars + B_RES, 0);
    if (tid == 32 && bid >= XP) asm volatile("cp.async.bulk.prefetch.L2.global [%0], 32768;" ::"l"(xin + (size_t)bid * 16384) : "memory");
    cluster_sync();
    if (tid == 224) {
      for (int i = 0; i < 4; i++) mbar_expect_tx(bars + B_XF + i * 8, 32768);
      issue_x(&tmX, sb + R_X + r * 32768, bars + B_XF + r * 8, 0, r);
      issue_x(&tmX, sb + R_X + 65536 + r * 32768, bars + B_XF + 16 + r * 8, 1, r);
    }
    const uint32_t near = UNI(__float_as_uint(lds4f(sb + R_SB)));
    __syncthreads();
    if (tid == 64) mbar_expect_tx(bars + B_PAIR, 512);
    sts8f(sb + R_VT2 + tid * 8, __uint_as_float(near + (wg << 20) + t7 * 16), __uint_as_float(wpage(L_VM + head) + r * 2048 + tid * 8));
    sts8f(sb + R_VT3 + tid * 8, __uint_as_float((wpage(L_U + r * 8 + warp) ^ near) + lane * 16), __uint_as_float((wpage(L_FLAG) ^ near) + lane * 8));
#define T8 ((t16 + sb) >> 1)
    const int idx = tid & 63;
    const int tk = idx & 3, pj = (idx >> 2) & 3, pc = idx >> 4;
    const uint32_t moff0 = wpage(L_MEM + (head >> 3)) + (head & 7) * 512 + r * 256 + (tk * 16 + pc * 4 + pj) * 4;
    sts16(t16_ + R_VT, make_uint4(ws0, sb + R_OB + warp * 1024 + (g >> 1) * 128 + (((((g ^ (g >> 2)) & 1) << 2) | c) << 4), moff0,
                                  sb + R_OB + (pj * 2 + (pc >> 1)) * 128 + (tk & 1) * 8 +
                                      (((((pc ^ pj) & 1) << 2) | ((((warp < 2) ? (r ^ 1) : r) ^ (pj >> 1)) << 1) | (tk >> 1)) << 4)));
    const uint32_t rdelta = UNI(mapa(sb, r ^ 1) - sb);
    auto vproj = [&](int n, float* d, bool gate, auto wg_c) __attribute__((always_inline)) {
      constexpr int wg = decltype(wg_c)::value;
      mbar_wait(bars + B_XF + (n & 1) * 16 + wg * 8, (n >> 1) & 1);
      const uint32_t z = wg * 2048, zx = z + (n & 1) * 4096;
      WG_FENCE();
#pragma unroll
      for (int k = 0; k < 32; k++) {
        const uint64_t b = cdesc(zx, R_X + xk(k));
        if (k == 0) wg_rs32<0>(d, w + 128, b);
        else if (k < 16) wg_rs32<1>(d, w + 128 + k * 4, b);
        else wg_ss32(d, cdesc(z, R_WS + (k - 16) * 2048), b);
        if (gate && k == VB - 1) bar_sync(5, 256);
      }
      WG_COMMIT();
    };
    auto vproj1 = [&](int n, bool gate) __attribute__((always_inline)) {
      float d[16];
      vproj(n, d, gate, IntC<1>());
      WG_WAIT(0);
      acc_fence16(d);
#pragma unroll
      for (int i = 0; i < 4; i++) sts16f(t16_ + (R_OB - 2048) + i * 2048, d[4 * i], d[4 * i + 1], d[4 * i + 2], d[4 * i + 3]);
    };
    auto vproj0 = [&](int n) __attribute__((always_inline)) {
      float d[16];
      vproj(n, d, false, IntC<0>());
      BASES();
      float4 p[4];
#pragma unroll
      for (int i = 0; i < 4; i++) p[i] = lds16f(t16 + R_OB + i * 2048);
      uint4* dst = goff(g_rings.vx[n & 3] + cta * 256, t16 - sb);
      WG_WAIT(0);
      acc_fence16(d);
      st_relaxed16(dst, make_uint4(pack_bf16(d[0] + p[0].x, d[1] + p[0].y), pack_bf16(d[4] + p[1].x, d[5] + p[1].y),
                                   pack_bf16(d[8] + p[2].x, d[9] + p[2].y), pack_bf16(d[12] + p[3].x, d[13] + p[3].y)));
      st_relaxed16(dst + 128, make_uint4(pack_bf16(d[2] + p[0].z, d[3] + p[0].w), pack_bf16(d[6] + p[1].z, d[7] + p[1].w),
                                         pack_bf16(d[10] + p[2].z, d[11] + p[2].w), pack_bf16(d[14] + p[3].z, d[15] + p[3].w)));
    };
    auto resets = [&](int s) __attribute__((always_inline)) {
      BASES();
      char* r0 = G + (lds4(T8 + R_VT2 + 4) + (((s + 2) & 3) << 14) + ((t16 - sb) >> 1) - 2048);
      char* r0b = other(r0);
      uint4* r1 = goff(g_rings.vx[(s + 3) & 3] + cta * 256, t16 - sb - 2048);
      char* r2 = G + ((lds4(t16 + R_VT + 8) ^ (warp < 6 ? 4096 : 0)) + (((s + 3) & 3) << 14));
      const uint4 e = make_uint4(SENT, SENT, SENT, SENT);
      st_relaxed16(r0, e); st_relaxed16(r0b, e); st_relaxed16(r1, e); st_relaxed16(r1 + 128, e);
      st_relaxed4(r2, SENT);
      const uint32_t rb = ld_relaxed4(r0) & ld_relaxed4(r0b) & ld_relaxed4(r1) & ld_relaxed4(r1 + 128) & ld_relaxed4(r2);
      if (__any_sync(~0u, rb != SENT)) FAIL(6001);
    };
    if (wg) vproj1(0, false);
    __syncthreads();
    if (wg == 0) vproj0(0);
    __syncthreads();
    if (wg) vproj1(1, false);
    if (warp < 4) {
      uint32_t m0 = reinterpret_cast<const uint32_t*>(mem0)[(4 * r + tk) * (DM / 2) + head * 16 + pj * 4 + pc];
      st_relaxed4(G + (moff0 ^ (warp < 2 ? 4096 : 0)), m0 == SENT ? 0x7FFF7FFFu : m0);
    }
    auto next_x = [&](int s) __attribute__((always_inline)) {
      if (t16_ == sb + 64 * 16 && s + 2 < NSEG) {
        mbar_expect_tx(bars + B_XF + (s & 1) * 16, 32768); mbar_expect_tx(bars + B_XF + (s & 1) * 16 + 8, 32768);
        issue_x(&tmX, sb + R_X + (s & 1) * 65536 + r * 32768, bars + B_XF + (s & 1) * 16 + r * 8, s + 2, r);
      }
      __syncwarp();
    };
    cluster_sync();
#pragma unroll 1
    for (int s = 0; s < NSEG; s++) {
      {
        float a0[4];
        BASES();
        const uint32_t mb = l16 + R_MEM + wg * 8192, ws = lds4(t16 + R_VT);
        const uint2 tm = lds8(T8 + R_VT2);
        const char* src = G + (tm.x + ((s & 3) << 14));
        auto tr = [&]() __attribute__((always_inline)) { TR(0); if (XV == 1) next_x(s); };
        auto gate = [&]() __attribute__((always_inline)) { if (s > 0) spin_gt(lds4(sb + R_BARS + 128)); TR(12); };
        switch (w4) {
          case 0: gemv_v<0>(w, src, a0, mb, ws, gate, tr); break;
          case 1: gemv_v<1>(w, src, a0, mb, ws, gate, tr); break;
          case 2: gemv_v<2>(w, src, a0, mb, ws, gate, tr); break;
          default: gemv_v<3>(w, src, a0, mb, ws, gate, tr); break;
        }
        char* vp = G + (tm.y + ((s & 3) << 14));
        const uint32_t m0 = pack_bf16(a0[0], a0[1]), m1 = pack_bf16(a0[2], a0[3]);
        st_relaxed8(vp, m0, m1);
        st_relaxed8(other(vp), m0, m1);
        TR(1);
        if (s == NSEG - 1) break;
        if (XV == 0 && wg == 0) next_x(s);
      }
      if (wg == 0) vproj0(s + 1); else resets(s);
      TR(2);
      if (warp == 7) {
        BASES();
        const uint32_t t = last_exchange(G + lds4(T8 + R_VT3 + 4), s);
        sts4f(sb + R_BARS + 128, __uint_as_float(t + d_m));
        spin_gt(t + d_u);
      }
      {
        BASES();
        const char* usrc = G + (lds4(T8 + R_VT3) + ((s & 3) << 14));
        const uint32_t owr = lds4(t16 + R_VT + 4);
        keep64(usrc);
        bar_sync(4, 256);
        if (wg) usrc += idle<USTAG / 5>(t16 & zero);
        TR(4);
        gemv_o(w, usrc, owr);
        TR(5);
        const uint2 tv = lds8(t16 + R_VT + 8);
        bar_sync(3, 256);
        if (wg == 0) {
          float2 p[8];
#pragma unroll
          for (int i = 0; i < 8; i++) p[i] = lds8f(tv.y + i * 1024);
          char* mp = G + (tv.x + (((s + 1) & 3) << 14));
          const uint32_t rbuf = ((t16 >> 1) & 504) + sb + R_SB;
          const float sx = ((p[0].x + p[1].x) + (p[2].x + p[3].x)) + ((p[4].x + p[5].x) + (p[6].x + p[7].x));
          const float sy = ((p[0].y + p[1].y) + (p[2].y + p[3].y)) + ((p[4].y + p[5].y) + (p[6].y + p[7].y));
          st_async8_if(rbuf + rdelta, sx, sy, bars + B_PAIR + rdelta, warp < 2);
          TR(6);
          if (warp >= 2) {
            mbar_wait(bars + B_PAIR, s & 1);
            TR(7);
            const float2 q = lds8f(rbuf);
            const uint32_t m = pack_bf16(sx + q.x, sy + q.y);
            st_relaxed4(mp, m);
            st_relaxed4(other(mp), m);
            TR(8);
            __syncwarp();
            mbar_arrive_tx_if(bars + B_PAIR, 512, t16 == sb + 64 * 16);
            __syncwarp();
          }
          bar_arrive(5, 256);
        } else {
          TR(6);
          if (s + 2 < NSEG) vproj1(s + 2, true); else bar_sync(5, 256);
          TR(7);
        }
      }
      __syncwarp();
      TRD();
    }
  }
  __syncwarp();
  cluster_sync();
  if (threadIdx.x == 0) STAMP(2);
}

__device__ uint32_t g_z1[512 * S_LEN];
__device__ uint32_t g_z2[512 * S_LEN];
__device__ __align__(16) uint32_t g_wt[513 * S_LEN];

__device__ __forceinline__ float2 cmul(float2 a, float2 b) { return make_float2(fmaf(a.x, b.x, -a.y * b.y), fmaf(a.x, b.y, a.y * b.x)); }
__device__ __forceinline__ float2 unpack_bf16(uint32_t v) { return make_float2(__uint_as_float(v << 16), __uint_as_float(v & 0xFFFF0000u)); }
__host__ __device__ constexpr float cos32(int i) {
  return i == 0 ? 1.f : i == 1 ? 0.98078528040323044913f : i == 2 ? 0.92387953251128675613f : i == 3 ? 0.83146961230254523708f
       : i == 4 ? 0.70710678118654752440f : i == 5 ? 0.55557023301960222474f : i == 6 ? 0.38268343236508977173f
       : i == 7 ? 0.19509032201612826785f : 0.f;
}
template <int I, int DIR> __device__ __forceinline__ float2 rot32(float2 v) {
  if constexpr (I == 0) return v;
  else if constexpr (I == 8) return DIR > 0 ? make_float2(-v.y, v.x) : make_float2(v.y, -v.x);
  else {
    constexpr float cs = I < 8 ? cos32(I) : -cos32(16 - I);
    constexpr float sn = (I < 8 ? cos32(8 - I) : cos32(I - 8)) * DIR;
    if constexpr (I == 4 || I == 12) {
      constexpr float sgn = (cs > 0) == (sn > 0) ? 1.f : -1.f;
      return make_float2(cs * (v.x - sgn * v.y), cs * (v.y + sgn * v.x));
    } else return make_float2(fmaf(v.x, cs, -v.y * sn), fmaf(v.x, sn, v.y * cs));
  }
}
template <int N, int DIR, int K> struct Comb {
  static __device__ __forceinline__ void run(const float2* e, const float2* o, float2* out) {
    if constexpr (K < N / 2) {
      const float2 t = rot32<K * (32 / N), DIR>(o[K]);
      out[K] = make_float2(e[K].x + t.x, e[K].y + t.y);
      out[K + N / 2] = make_float2(e[K].x - t.x, e[K].y - t.y);
      Comb<N, DIR, K + 1>::run(e, o, out);
    }
  }
};
template <int N, int DIR, int ST> __device__ __forceinline__ void fft_r(const float2* in, float2* out) {
  if constexpr (N == 1) out[0] = in[0];
  else {
    float2 e[N / 2], o[N / 2];
    fft_r<N / 2, DIR, ST * 2>(in, e);
    fft_r<N / 2, DIR, ST * 2>(in + ST, o);
    Comb<N, DIR, 0>::run(e, o, out);
  }
}
template <int N, int DIR> __device__ __forceinline__ void fft_reg(float2* v) {
  float2 t[N];
  fft_r<N, DIR, 1>(v, t);
#pragma unroll
  for (int i = 0; i < N; i++) v[i] = t[i];
}
template <int N> __device__ __forceinline__ void twiddle(float2* v, float x) {
  float2 p[N];
  sincospif(x, &p[1].y, &p[1].x);
#pragma unroll
  for (int k = 2; k < N; k++) p[k] = cmul(p[k / 2], p[k - k / 2]);
#pragma unroll
  for (int k = 1; k < N; k++) v[k] = cmul(v[k], p[k]);
}

constexpr int F1_LD = 16 * 33 - 1;
constexpr int F1_SMEM = 16 * F1_LD * 8;
__device__ __forceinline__ void fft_rows_fwd(float2* fs, int item, const bf16* __restrict__ x, const bf16* __restrict__ wr, const bf16* __restrict__ wi) {
  const int tid = threadIdx.x, s0 = item * 16;
  {
    const int row = tid >> 4, t = tid & 15;
    const uint2* src = reinterpret_cast<const uint2*>(x + (size_t)(s0 + row) * DM) + t;
    float2 a[16], b[16];
#pragma unroll
    for (int i = 0; i < 16; i++) { const uint2 v = __ldg(src + i * 16); a[i] = unpack_bf16(v.x); b[i] = unpack_bf16(v.y); }
    fft_reg<16, -1>(a); twiddle<16>(a, -(float)(2 * t) / 256.f);
    float2* d = fs + row * F1_LD + t;
#pragma unroll
    for (int i = 0; i < 16; i++) d[i * 33] = a[i];
    fft_reg<16, -1>(b); twiddle<16>(b, -(float)(2 * t + 1) / 256.f);
#pragma unroll
    for (int i = 0; i < 16; i++) d[i * 33 + 16] = b[i];
  }
  __syncthreads();
  {
    const int row = tid & 15, k2 = tid >> 4;
    float2 v[32];
#pragma unroll
    for (int i = 0; i < 32; i++) v[i] = fs[row * F1_LD + k2 * 33 + (i >> 1) + (i & 1) * 16];
    fft_reg<32, -1>(v);
#pragma unroll
    for (int i = 0; i < 32; i++) g_z1[(k2 + 16 * i) * S_LEN + s0 + row] = pack_bf16(v[i].x, v[i].y);
  }
  {
    __syncthreads();
    uint4* sw = reinterpret_cast<uint4*>(fs);
    const uint4* pr = reinterpret_cast<const uint4*>(wr + (size_t)s0 * 513);
    const uint4* pi = reinterpret_cast<const uint4*>(wi + (size_t)s0 * 513);
#pragma unroll
    for (int q = 0; q < 5; q++) {
      const int i = tid + q * 256;
      if (i < 1026) { sw[i] = __ldg(pr + i); sw[1026 + i] = __ldg(pi + i); }
    }
    __syncthreads();
    const uint16_t* hr = reinterpret_cast<const uint16_t*>(fs) + (tid & 3) * 4 * 513;
    const uint16_t* hi = hr + 1026 * 8;
#pragma unroll
    for (int q = 0; q < 9; q++) {
      const int k = (tid >> 2) + q * 64;
      if (q == 8 && k != 512) break;
      uint32_t o[4];
#pragma unroll
      for (int r = 0; r < 4; r++) o[r] = (uint32_t)hr[r * 513 + k] | ((uint32_t)hi[r * 513 + k] << 16);
      *reinterpret_cast<uint4*>(g_wt + k * S_LEN + s0 + (tid & 3) * 4) = make_uint4(o[0], o[1], o[2], o[3]);
    }
  }
}

constexpr int F2_LD = 2048 + 128;
__device__ __forceinline__ int f2_pad(int i) { return i + (i >> 7); }
__device__ __forceinline__ void fft_cols(float2* fs, int item) {
  const int tid = threadIdx.x, half = tid >> 7, t = tid & 127;
  const int k = item == 0 ? half * 256 : (half ? 512 - item : item);
  float2* my = fs + half * F2_LD;
  const float2* mir = fs + (item == 0 ? half : half ^ 1) * F2_LD;
  float2 v[16];
#pragma unroll
  for (int a = 0; a < 16; a++) v[a] = unpack_bf16(__ldcg(&g_z1[k * S_LEN + t + 128 * a]));
  fft_reg<16, -1>(v); twiddle<16>(v, -(float)t / 1024.f);
#pragma unroll
  for (int i = 0; i < 16; i++) my[f2_pad(i * 128 + t)] = v[i];
  bar_sync(1 + half, 128);
  const int t0 = t & 15, kp = t >> 4;
#pragma unroll
  for (int h = 0; h < 2; h++) {
#pragma unroll
    for (int b = 0; b < 8; b++) v[h * 8 + b] = my[f2_pad((2 * kp + h) * 128 + t0 + 16 * b)];
    fft_reg<8, -1>(v + h * 8);
  }
  float2 p8[8];
  sincospif(-(float)t0 / 64.f, &p8[1].y, &p8[1].x);
#pragma unroll
  for (int i = 2; i < 8; i++) p8[i] = cmul(p8[i / 2], p8[i - i / 2]);
#pragma unroll
  for (int h = 0; h < 2; h++)
#pragma unroll
    for (int b = 0; b < 8; b++)
      my[f2_pad((2 * kp + h) * 128 + t0 + 16 * b)] = b ? cmul(v[h * 8 + b], p8[b]) : v[h * 8];
  uint32_t wa[16], wb[16];
#pragma unroll
  for (int m = 0; m < 16; m++) {
    wa[m] = __ldcg(&g_wt[k * S_LEN + t + 128 * m]);
    wb[m] = __ldcg(&g_wt[(512 - k) * S_LEN + ((2048 - t - 128 * m) & 2047)]);
  }
  bar_sync(1 + half, 128);
  const int base3 = (t & 15) * 128 + (t >> 4) * 16;
#pragma unroll
  for (int i = 0; i < 16; i++) v[i] = my[f2_pad(base3 + i)];
  fft_reg<16, -1>(v);
  bar_sync(1 + half, 128);
#pragma unroll
  for (int m = 0; m < 16; m++) my[t + 128 * m] = v[m];
  __syncthreads();
  {
    float sn, cs;
    sincospif((float)k / 512.f, &sn, &cs);
    const float sc = 0.5f / (2048.f * 512.f);
#pragma unroll
    for (int m = 0; m < 16; m++) {
      const int j = t + 128 * m, jm = (2048 - j) & 2047;
      float2 A = unpack_bf16(wa[m]), B = unpack_bf16(wb[m]);
      B.y = -B.y;
      if (k == 0) {
        const float2 A2 = unpack_bf16(__ldcg(&g_wt[jm])), B2 = unpack_bf16(__ldcg(&g_wt[512 * S_LEN + j]));
        A = make_float2(0.5f * (A.x + A2.x), 0.5f * (A.y - A2.y));
        B = make_float2(0.5f * (B.x + B2.x), 0.5f * (B.y + B2.y));
      }
      const float2 df = make_float2((A.x - B.x) * sc, (A.y - B.y) * sc);
      const float2 ca = make_float2(fmaf(-sn, df.x, (A.x + B.x) * sc), fmaf(-sn, df.y, (A.y + B.y) * sc));
      const float2 cb = make_float2(-cs * df.y, cs * df.x);
      float2 zc = mir[jm];
      zc.y = -zc.y;
      const float2 r1 = cmul(ca, v[m]), r2 = cmul(cb, zc);
      v[m] = make_float2(r1.x + r2.x, r1.y + r2.y);
    }
  }
  fft_reg<16, 1>(v);
  __syncthreads();
#pragma unroll
  for (int i = 0; i < 16; i++) my[f2_pad(base3 + i)] = v[i];
  bar_sync(1 + half, 128);
#pragma unroll
  for (int h = 0; h < 2; h++) {
#pragma unroll
    for (int b = 0; b < 8; b++) {
      const float2 z = my[f2_pad((2 * kp + h) * 128 + t0 + 16 * b)];
      v[h * 8 + b] = b ? cmul(z, make_float2(p8[b].x, -p8[b].y)) : z;
    }
    fft_reg<8, 1>(v + h * 8);
#pragma unroll
    for (int b = 0; b < 8; b++) my[f2_pad((2 * kp + h) * 128 + t0 + 16 * b)] = v[h * 8 + b];
  }
  bar_sync(1 + half, 128);
#pragma unroll
  for (int i = 0; i < 16; i++) v[i] = my[f2_pad(i * 128 + t)];
  twiddle<16>(v, (float)t / 1024.f);
  fft_reg<16, 1>(v);
#pragma unroll
  for (int a = 0; a < 16; a++) g_z2[k * S_LEN + t + 128 * a] = pack_bf16(v[a].x, v[a].y);
}

__device__ __forceinline__ void fft_rows_inv(float2* fs, int item, bf16* __restrict__ out) {
  const int tid = threadIdx.x, s0 = item * 16;
  {
    const int row = tid & 15, k2 = tid >> 4;
    float2 v[32];
#pragma unroll
    for (int i = 0; i < 32; i++) v[i] = unpack_bf16(__ldcg(&g_z2[(k2 + 16 * i) * S_LEN + s0 + row]));
    fft_reg<32, 1>(v);
#pragma unroll
    for (int i = 0; i < 32; i++) fs[row * F1_LD + k2 * 33 + (i >> 1) + (i & 1) * 16] = v[i];
  }
  __syncthreads();
  {
    const int row = tid >> 4, t = tid & 15;
    const float2* d = fs + row * F1_LD + t;
    float2 a[16], b[16];
#pragma unroll
    for (int i = 0; i < 16; i++) { a[i] = d[i * 33]; b[i] = d[i * 33 + 16]; }
    twiddle<16>(a, (float)(2 * t) / 256.f); fft_reg<16, 1>(a);
    twiddle<16>(b, (float)(2 * t + 1) / 256.f); fft_reg<16, 1>(b);
    uint2* dst = reinterpret_cast<uint2*>(out + (size_t)(s0 + row) * OUT_LD) + t;
#pragma unroll
    for (int i = 0; i < 16; i++) dst[i * 16] = make_uint2(pack_bf16(a[i].x, a[i].y), pack_bf16(b[i].x, b[i].y));
  }
}

__global__ void __maxnreg__(112) fft_all(const bf16* __restrict__ x, const bf16* __restrict__ wr, const bf16* __restrict__ wi, bf16* __restrict__ out) {
  extern __shared__ float2 fs[];
  volatile int& s_item = *reinterpret_cast<volatile int*>(fs + 15 * F1_LD + 14 * 33 + 32);
  asm volatile("griddepcontrol.launch_dependents;" ::: "memory");
  int* ctr = &g_rings.ctr[0][0];
  int phase = 0, cnt = 0;
  for (;;) {
    __syncthreads();
    if (threadIdx.x == 0) {
      const int it = atomicAdd(ctr, 1) + 1;
      const int ph = (it >= 128) + (it >= 384) + (it >= 512);
      if (ph != phase) {
        if (cnt) { __threadfence(); atomicAdd(ctr + 32 + phase * 32, cnt); }
        const int target = ph == 1 ? 127 : 255;
        for (int i = 0; ph < 3 && i < (1 << 22); i++) {
          int v; asm volatile("ld.acquire.gpu.global.s32 %0, [%1];" : "=r"(v) : "l"(ctr + ph * 32) : "memory");
          if (v == target) break;
          __nanosleep(100);
        }
        phase = ph; cnt = 0;
      }
      cnt += ph < 2;
      if (it == 128) STAMP(5);
      if (it == 384) STAMP(6);
      if (it >= 512) STAMP(7);
      s_item = it;
    }
    __syncthreads();
    const int it = s_item;
    if (it >= 512) break;
    if (it < 128) {
      const int nx = it + (int)gridDim.x;
      if (nx < 128) {
        asm volatile("prefetch.global.L2 [%0];" ::"l"(x + (size_t)nx * 16 * DM + threadIdx.x * 64));
        asm volatile("prefetch.global.L2 [%0];" ::"l"((threadIdx.x < 128 ? wr : wi) + (size_t)nx * 16 * 513 + (threadIdx.x & 127) * 64));
      }
      fft_rows_fwd(fs, it, x, wr, wi);
    }
    else if (it < 384) fft_cols(fs, it - 128);
    else fft_rows_inv(fs, it - 384, out);
  }
  if (blockIdx.x == 0) asm volatile("griddepcontrol.wait;" ::: "memory");
}

typedef CUresult (*EncodeFn)(CUtensorMap*, CUtensorMapDataType, cuuint32_t, void*, const cuuint64_t*, const cuuint64_t*,
                             const cuuint32_t*, const cuuint32_t*, CUtensorMapInterleave, CUtensorMapSwizzle,
                             CUtensorMapL2promotion, CUtensorMapFloatOOBfill);
static EncodeFn g_encode;
static CUtensorMap make_map(const void* p, uint64_t cols, uint64_t rows, uint64_t ld, uint32_t bc, uint32_t br, bool swz) {
  CUtensorMap m;
  cuuint64_t dims[2] = {cols, rows}, st[1] = {ld * 2};
  cuuint32_t box[2] = {bc, br}, es[2] = {1, 1};
  g_encode(&m, CU_TENSOR_MAP_DATA_TYPE_BFLOAT16, 2, const_cast<void*>(p), dims, st, box, es, CU_TENSOR_MAP_INTERLEAVE_NONE,
           swz ? CU_TENSOR_MAP_SWIZZLE_128B : CU_TENSOR_MAP_SWIZZLE_NONE, CU_TENSOR_MAP_L2_PROMOTION_L2_256B,
           CU_TENSOR_MAP_FLOAT_OOB_FILL_NONE);
  return m;
}
template <typename... KA, typename... A>
static void launch(void (*k)(KA...), dim3 grid, dim3 block, size_t smem, int cluster, bool pdl, cudaStream_t st, A... args) {
  cudaLaunchConfig_t cfg = {};
  cfg.gridDim = grid; cfg.blockDim = block; cfg.dynamicSmemBytes = smem; cfg.stream = st;
  cudaLaunchAttribute at[2]; int n = 0;
  if (cluster > 1) { at[n].id = cudaLaunchAttributeClusterDimension; at[n].val.clusterDim.x = cluster; at[n].val.clusterDim.y = 1; at[n].val.clusterDim.z = 1; n++; }
  if (pdl) { at[n].id = cudaLaunchAttributeProgrammaticStreamSerialization; at[n].val.programmaticStreamSerializationAllowed = 1; n++; }
  cfg.attrs = at; cfg.numAttrs = n;
  cudaLaunchKernelEx(&cfg, k, args...);
}
#define PARAM(n, d) (d)

extern "C" void kernel_launch(void* const* d_in, const int* in_sizes, int n_in, void* d_out, int out_size) {
  const bf16* Ax = (const bf16*)d_in[0]; const bf16* Awr = (const bf16*)d_in[1]; const bf16* Awi = (const bf16*)d_in[2];
  const bf16* Bx = (const bf16*)d_in[3]; const bf16* mem0 = (const bf16*)d_in[4];
  const bf16* Wq = (const bf16*)d_in[5]; const bf16* Wk = (const bf16*)d_in[6]; const bf16* Wv = (const bf16*)d_in[7];
  const bf16* Wo = (const bf16*)d_in[8];
  bf16* out = (bf16*)d_out;
  if (!g_encode) {
    cudaDriverEntryPointQueryResult qr;
    cudaGetDriverEntryPoint("cuTensorMapEncodeTiled", (void**)&g_encode, cudaEnableDefault, &qr);
    cudaFuncSetAttribute(gemm_kernel, cudaFuncAttributeMaxDynamicSharedMemorySize, G_SMEM);
    cudaFuncSetAttribute(rec_kernel, cudaFuncAttributeMaxDynamicSharedMemorySize, R_SMEM);
    cudaFuncSetAttribute(fft_all, cudaFuncAttributeMaxDynamicSharedMemorySize, F1_SMEM);
  }
  void *p_ux, *p_rings, *p_win;
  cudaGetSymbolAddress(&p_ux, g_ux); cudaGetSymbolAddress(&p_rings, g_rings); cudaGetSymbolAddress(&p_win, g_win);
  char* win = (char*)(((uintptr_t)p_win + (2u << 20) - 1) & ~(uintptr_t)((2u << 20) - 1));
  const CUtensorMap rWq = make_map(Wq, HD, DM, HD, 64, 128, true), rWk = make_map(Wk, HD, DM, HD, 64, 128, true),
                    rWv = make_map(Wv, HD, DM, HD, 64, 128, true), rWo = make_map(Wo, DM, HD, DM, 32, 256, false);
  CUtensorMap rX;
  {
    cuuint64_t dims[3] = {64, S_LEN, 16}, st[2] = {DM * 2, 128};
    cuuint32_t box[3] = {64, 32, 8}, es[3] = {1, 1, 1};
    g_encode(&rX, CU_TENSOR_MAP_DATA_TYPE_BFLOAT16, 3, const_cast<bf16*>(Bx), dims, st, box, es, CU_TENSOR_MAP_INTERLEAVE_NONE,
             CU_TENSOR_MAP_SWIZZLE_128B, CU_TENSOR_MAP_L2_PROMOTION_L2_256B, CU_TENSOR_MAP_FLOAT_OOB_FILL_NONE);
  }
  const CUtensorMap mU = make_map(p_ux, HD, S_LEN, HD, 64, 64, true), mWo = make_map(Wo, DM, HD, DM, 64, 64, true);
  const CUtensorMap mOut = make_map(out, OUT_LD, S_LEN, OUT_LD, 64, 64, true);
  cudaStream_t st = cudaStreamPerThread;
  launch(rec_kernel, dim3(128), dim3(256), R_SMEM, 2, false, st, rWq, rWk, rWv, rWo, rX, mem0, Bx, win, (int)PARAM("DU", 750), (int)PARAM("DM", 1850), (int)PARAM("DQ", 1790), 0);
  if (PARAM("BG", 8)) launch(fft_all, dim3(PARAM("BG", 8)), dim3(256), F1_SMEM, 1, true, st, Ax, Awr, Awi, out);
  launch(gemm_kernel, dim3(8, 16), dim3(288), G_SMEM, 2, true, st, mU, mWo, mWo, mWo, mOut, 8, 64, 1024, (const int*)((char*)p_rings + offsetof(Rings, ctr) + 3 * 128));
  if (PARAM("TAIL", 128)) launch(fft_all, dim3(PARAM("TAIL", 128)), dim3(256), F1_SMEM, 1, true, st, Ax, Awr, Awi, out);
}
```

```cpp
#include <cuda_runtime.h>
#include <cuda_bf16.h>
#include <cuda.h>
#include <stdint.h>

typedef __nv_bfloat16 bf16;

constexpr int S_LEN = 2048, DM = 1024, NH = 32, DH = 128, HD = 4096, NMEM = 8, SEG = 32, NSEG = 64;
constexpr int OUT_LD = 2048;
constexpr uint32_t SENT = 0xFFFFFFFFu;

__device__ __forceinline__ uint32_t smem_u32(const void* p) { return (uint32_t)__cvta_generic_to_shared(p); }
__device__ __forceinline__ void mbar_init(uint32_t bar, uint32_t cnt) {
  asm volatile("mbarrier.init.shared::cta.b64 [%0], %1;" ::"r"(bar), "r"(cnt) : "memory");
}
__device__ __forceinline__ void mbar_expect_tx(uint32_t bar, uint32_t bytes) {
  asm volatile("mbarrier.arrive.expect_tx.shared::cta.b64 _, [%0], %1;" ::"r"(bar), "r"(bytes) : "memory");
}
__device__ __forceinline__ void mbar_arrive(uint32_t bar) {
  asm volatile("mbarrier.arrive.shared::cta.b64 _, [%0];" ::"r"(bar) : "memory");
}
__device__ __forceinline__ void mbar_arrive_tx_if(uint32_t bar, uint32_t bytes, uint32_t cond) {
  asm volatile("{.reg .pred q; setp.ne.u32 q, %2, 0; @q mbarrier.arrive.expect_tx.shared::cta.b64 _, [%0], %1;}" ::"r"(bar), "r"(bytes), "r"(cond) : "memory");
}
__device__ __forceinline__ void mbar_arrive_cluster(uint32_t bar_cluster_addr) {
  asm volatile("mbarrier.arrive.shared::cluster.b64 _, [%0];" ::"r"(bar_cluster_addr) : "memory");
}
__device__ __forceinline__ bool mbar_try(uint32_t bar, uint32_t par) {
  uint32_t ok;
  asm volatile("{.reg .pred p; mbarrier.try_wait.parity.shared::cta.b64 p, [%1], %2; selp.u32 %0, 1, 0, p;}"
               : "=r"(ok) : "r"(bar), "r"(par) : "memory");
  return ok;
}
#define FAIL(id) do { asm volatile("trap; exit;"); __builtin_unreachable(); } while (0)
__device__ __forceinline__ void mbar_wait(uint32_t bar, uint32_t par) {
  if (__builtin_expect(!mbar_try(bar, par), 0)) {
    int it = 0;
    while (!mbar_try(bar, par)) { if (++it > (1 << 18)) FAIL((bar & 255) + par * 1000); }
  }
}
__device__ __forceinline__ void tma2d(uint32_t dst, const CUtensorMap* tm, int c0, int c1, uint32_t bar) {
  asm volatile("cp.async.bulk.tensor.2d.shared::cluster.global.mbarrier::complete_tx::bytes [%0], [%1, {%3, %4}], [%2];"
               ::"r"(dst), "l"(tm), "r"(bar), "r"(c0), "r"(c1) : "memory");
}
__device__ __forceinline__ void tma2d_ef(uint32_t dst, const CUtensorMap* tm, int c0, int c1, uint32_t bar) {
  asm volatile("cp.async.bulk.tensor.2d.shared::cluster.global.mbarrier::complete_tx::bytes.L2::cache_hint [%0], [%1, {%3, %4}], [%2], %5;"
               ::"r"(dst), "l"(tm), "r"(bar), "r"(c0), "r"(c1), "l"(0x12F0000000000000ull) : "memory");
}
__device__ __forceinline__ void tma2d_mc(uint32_t dst, const CUtensorMap* tm, int c0, int c1, uint32_t bar, uint16_t mask) {
  asm volatile("cp.async.bulk.tensor.2d.shared::cluster.global.mbarrier::complete_tx::bytes.multicast::cluster [%0], [%1, {%3, %4}], [%2], %5;"
               ::"r"(dst), "l"(tm), "r"(bar), "r"(c0), "r"(c1), "h"(mask) : "memory");
}
__device__ __forceinline__ void tma2d_store(const CUtensorMap* tm, uint32_t src, int c0, int c1) {
  asm volatile("cp.async.bulk.tensor.2d.global.shared::cta.bulk_group [%0, {%2, %3}], [%1];"
               ::"l"(tm), "r"(src), "r"(c0), "r"(c1) : "memory");
}
__device__ __forceinline__ uint32_t mapa(uint32_t a, uint32_t r) {
  uint32_t o; asm("mapa.shared::cluster.u32 %0, %1, %2;" : "=r"(o) : "r"(a), "r"(r)); return o;
}
__device__ __forceinline__ void st_async8(uint32_t addr, float a, float b, uint32_t bar) {
  asm volatile("st.async.weak.shared::cluster.mbarrier::complete_tx::bytes.v2.f32 [%0], {%1, %2}, [%3];"
               ::"r"(addr), "f"(a), "f"(b), "r"(bar) : "memory");
}
__device__ __forceinline__ void st_async8_if(uint32_t addr, float a, float b, uint32_t bar, uint32_t cond) {
  asm volatile("{.reg .pred q; setp.ne.u32 q, %4, 0; @q st.async.weak.shared::cluster.mbarrier::complete_tx::bytes.v2.f32 [%0], {%1, %2}, [%3];}"
               ::"r"(addr), "f"(a), "f"(b), "r"(bar), "r"(cond) : "memory");
}
__device__ __forceinline__ void st_async16(uint32_t addr, const float* v, uint32_t bar) {
  asm volatile("st.async.weak.shared::cluster.mbarrier::complete_tx::bytes.v4.f32 [%0], {%1, %2, %3, %4}, [%5];"
               ::"r"(addr), "f"(v[0]), "f"(v[1]), "f"(v[2]), "f"(v[3]), "r"(bar) : "memory");
}
__device__ __forceinline__ void st_async4(uint32_t addr, float a, uint32_t bar) {
  asm volatile("st.async.weak.shared::cluster.mbarrier::complete_tx::bytes.f32 [%0], %1, [%2];"
               ::"r"(addr), "f"(a), "r"(bar) : "memory");
}
__device__ __forceinline__ void cluster_sync() {
  asm volatile("barrier.cluster.arrive.release.aligned; barrier.cluster.wait.acquire.aligned;" ::: "memory");
}
__device__ __forceinline__ void bar_sync(int id, int n) { asm volatile("bar.sync %0, %1;" ::"r"(id), "r"(n) : "memory"); }
__device__ __forceinline__ void ldsm4(uint32_t& r0, uint32_t& r1, uint32_t& r2, uint32_t& r3, uint32_t a) {
  asm volatile("ldmatrix.sync.aligned.m8n8.x4.shared.b16 {%0,%1,%2,%3}, [%4];"
               : "=r"(r0), "=r"(r1), "=r"(r2), "=r"(r3) : "r"(a) : "memory");
}
__device__ __forceinline__ void ldsm4t(uint32_t& r0, uint32_t& r1, uint32_t& r2, uint32_t& r3, uint32_t a) {
  asm volatile("ldmatrix.sync.aligned.m8n8.x4.trans.shared.b16 {%0,%1,%2,%3}, [%4];"
               : "=r"(r0), "=r"(r1), "=r"(r2), "=r"(r3) : "r"(a) : "memory");
}
__device__ __forceinline__ void stsm4(uint32_t a, uint32_t r0, uint32_t r1, uint32_t r2, uint32_t r3) {
  asm volatile("stmatrix.sync.aligned.m8n8.x4.shared.b16 [%0], {%1,%2,%3,%4};"
               ::"r"(a), "r"(r0), "r"(r1), "r"(r2), "r"(r3) : "memory");
}
__device__ __forceinline__ void stsm1(uint32_t a, uint32_t r0) {
  asm volatile("stmatrix.sync.aligned.m8n8.x1.shared.b16 [%0], {%1};" ::"r"(a), "r"(r0) : "memory");
}
__device__ __forceinline__ void mma16816(float* d, uint32_t a0, uint32_t a1, uint32_t a2, uint32_t a3, uint32_t b0, uint32_t b1) {
  asm volatile("mma.sync.aligned.m16n8k16.row.col.f32.bf16.bf16.f32 {%0,%1,%2,%3}, {%4,%5,%6,%7}, {%8,%9}, {%0,%1,%2,%3};"
               : "+f"(d[0]), "+f"(d[1]), "+f"(d[2]), "+f"(d[3])
               : "r"(a0), "r"(a1), "r"(a2), "r"(a3), "r"(b0), "r"(b1));
}
__device__ __forceinline__ void mma1688(float* d, uint32_t a0, uint32_t a1, uint32_t b0) {
  asm volatile("mma.sync.aligned.m16n8k8.row.col.f32.bf16.bf16.f32 {%0,%1,%2,%3}, {%4,%5}, {%6}, {%0,%1,%2,%3};"
               : "+f"(d[0]), "+f"(d[1]), "+f"(d[2]), "+f"(d[3]) : "r"(a0), "r"(a1), "r"(b0));
}
__device__ __forceinline__ uint32_t pack_bf16(float lo, float hi) {
  uint32_t r; asm("cvt.rn.bf16x2.f32 %0, %1, %2;" : "=r"(r) : "f"(hi), "f"(lo)); return r;
}
__device__ __forceinline__ uint4 ld_relaxed16(const void* p) {
  uint4 v;
  asm volatile("ld.relaxed.gpu.global.v4.u32 {%0,%1,%2,%3}, [%4];" : "=r"(v.x), "=r"(v.y), "=r"(v.z), "=r"(v.w) : "l"(p) : "memory");
  return v;
}
__device__ __forceinline__ uint4 ld_relaxed16b(const void* p) {
  uint4 v;
  asm volatile("ld.relaxed.gpu.global.v4.b32 {%0,%1,%2,%3}, [%4];" : "=r"(v.x), "=r"(v.y), "=r"(v.z), "=r"(v.w) : "l"(p) : "memory");
  return v;
}
__device__ __forceinline__ void ld_relaxed16_if(uint4& v, const void* p, uint32_t cond) {
  asm volatile("{.reg .pred q; setp.ne.u32 q, %5, 0; @q ld.relaxed.gpu.global.v4.u32 {%0,%1,%2,%3}, [%4];}"
               : "+r"(v.x), "+r"(v.y), "+r"(v.z), "+r"(v.w) : "l"(p), "r"(cond) : "memory");
}
__device__ __forceinline__ uint32_t ld_relaxed4(const void* p) {
  uint32_t v; asm volatile("ld.relaxed.gpu.global.u32 %0, [%1];" : "=r"(v) : "l"(p) : "memory"); return v;
}
__device__ __forceinline__ void st_relaxed4(void* p, uint32_t v) {
  asm volatile("st.relaxed.gpu.global.u32 [%0], %1;" ::"l"(p), "r"(v) : "memory");
}
__device__ __forceinline__ void st_relaxed4_if(void* p, uint32_t v, uint32_t cond) {
  asm volatile("{.reg .pred q; setp.ne.u32 q, %2, 0; @q st.relaxed.gpu.global.u32 [%0], %1;}" ::"l"(p), "r"(v), "r"(cond) : "memory");
}
__device__ __forceinline__ void sts16(uint32_t a, uint4 v) {
  asm volatile("st.shared.v4.u32 [%0], {%1,%2,%3,%4};" ::"r"(a), "r"(v.x), "r"(v.y), "r"(v.z), "r"(v.w) : "memory");
}
__device__ __forceinline__ void sts4f(uint32_t a, float v) { asm volatile("st.shared.f32 [%0], %1;" ::"r"(a), "f"(v) : "memory"); }
__device__ __forceinline__ void sts8f(uint32_t a, float x, float y) { asm volatile("st.shared.v2.f32 [%0], {%1,%2};" ::"r"(a), "f"(x), "f"(y) : "memory"); }
__device__ __forceinline__ float lds4f(uint32_t a) { float v; asm volatile("ld.shared.f32 %0, [%1];" : "=f"(v) : "r"(a) : "memory"); return v; }
__device__ __forceinline__ float2 lds8f(uint32_t a) { float2 v; asm volatile("ld.shared.v2.f32 {%0,%1}, [%2];" : "=f"(v.x), "=f"(v.y) : "r"(a) : "memory"); return v; }
__device__ __forceinline__ uint32_t lds4(uint32_t a) { uint32_t v; asm volatile("ld.shared.u32 %0, [%1];" : "=r"(v) : "r"(a) : "memory"); return v; }
__device__ __forceinline__ uint2 lds8(uint32_t a) { uint2 v; asm volatile("ld.shared.v2.u32 {%0,%1}, [%2];" : "=r"(v.x), "=r"(v.y) : "r"(a) : "memory"); return v; }
__device__ __forceinline__ uint32_t umax4(uint4 v) { return max(max(v.x, v.y), max(v.z, v.w)); }
__device__ __forceinline__ float ex2(float x) { float y; asm("ex2.approx.ftz.f32 %0, %1;" : "=f"(y) : "f"(x)); return y; }

__device__ __forceinline__ void fence_gpu() { asm volatile("fence.acq_rel.gpu;" ::: "memory"); }
#define WG_FENCE() asm volatile("wgmma.fence.sync.aligned;" ::: "memory")
#define WG_COMMIT() asm volatile("wgmma.commit_group.sync.aligned;" ::: "memory")
#define WG_WAIT(n) asm volatile("wgmma.wait_group.sync.aligned " #n ";" ::: "memory")
__device__ __forceinline__ uint64_t mk_desc(uint32_t addr, uint32_t lbo, uint32_t sbo) {
  return (uint64_t)((addr >> 4) & 0x3FFF) | ((uint64_t)(lbo >> 4) << 16) | ((uint64_t)(sbo >> 4) << 32) | ((uint64_t)1 << 62);
}
__device__ __forceinline__ void stsm4t(uint32_t a, uint32_t r0, uint32_t r1, uint32_t r2, uint32_t r3) {
  asm volatile("stmatrix.sync.aligned.m8n8.x4.trans.shared.b16 [%0], {%1,%2,%3,%4};"
               ::"r"(a), "r"(r0), "r"(r1), "r"(r2), "r"(r3) : "memory");
}
__device__ __forceinline__ void sts16f(uint32_t a, float x, float y, float z, float w) {
  asm volatile("st.shared.v4.f32 [%0], {%1,%2,%3,%4};" ::"r"(a), "f"(x), "f"(y), "f"(z), "f"(w) : "memory");
}
__device__ __forceinline__ float4 lds16f(uint32_t a) {
  float4 v; asm volatile("ld.shared.v4.f32 {%0,%1,%2,%3}, [%4];" : "=f"(v.x), "=f"(v.y), "=f"(v.z), "=f"(v.w) : "r"(a) : "memory"); return v;
}
__device__ __forceinline__ uint4 lds16(uint32_t a) {
  uint4 v; asm volatile("ld.shared.v4.u32 {%0,%1,%2,%3}, [%4];" : "=r"(v.x), "=r"(v.y), "=r"(v.z), "=r"(v.w) : "r"(a) : "memory"); return v;
}
__device__ __forceinline__ uint4 lds16v(uint32_t a) {
  uint4 v; asm volatile("ld.volatile.shared.v4.u32 {%0,%1,%2,%3}, [%4];" : "=r"(v.x), "=r"(v.y), "=r"(v.z), "=r"(v.w) : "r"(a) : "memory"); return v;
}
__device__ __forceinline__ uint32_t lds4v(uint32_t a) { uint32_t v; asm volatile("ld.volatile.shared.u32 %0, [%1];" : "=r"(v) : "r"(a) : "memory"); return v; }
__device__ __forceinline__ float4 lds16fv(uint32_t a) {
  float4 v; asm volatile("ld.volatile.shared.v4.f32 {%0,%1,%2,%3}, [%4];" : "=f"(v.x), "=f"(v.y), "=f"(v.z), "=f"(v.w) : "r"(a) : "memory"); return v;
}
__device__ __forceinline__ uint4 lds16c(uint32_t a) {
  uint4 v; asm volatile("ld.volatile.shared::cluster.v4.u32 {%0,%1,%2,%3}, [%4];" : "=r"(v.x), "=r"(v.y), "=r"(v.z), "=r"(v.w) : "r"(a) : "memory"); return v;
}
__device__ __forceinline__ uint2 lds8v(uint32_t a) {
  uint2 v; asm volatile("ld.volatile.shared.v2.u32 {%0,%1}, [%2];" : "=r"(v.x), "=r"(v.y) : "r"(a) : "memory"); return v;
}
__device__ __forceinline__ uint2 ld_relaxed8(const void* p) {
  uint2 v; asm volatile("ld.relaxed.gpu.global.v2.u32 {%0,%1}, [%2];" : "=r"(v.x), "=r"(v.y) : "l"(p) : "memory"); return v;
}
__device__ __forceinline__ void st_relaxed8(void* p, uint32_t a, uint32_t b) {
  asm volatile("st.relaxed.gpu.global.v2.u32 [%0], {%1,%2};" ::"l"(p), "r"(a), "r"(b) : "memory");
}
__device__ __forceinline__ void st_relaxed16(void* p, uint4 v) {
  asm volatile("st.relaxed.gpu.global.v4.u32 [%0], {%1,%2,%3,%4};" ::"l"(p), "r"(v.x), "r"(v.y), "r"(v.z), "r"(v.w) : "memory");
}
__device__ __forceinline__ void bar_arrive(int id, int n) { asm volatile("bar.arrive %0, %1;" ::"r"(id), "r"(n) : "memory"); }
template <typename T> __device__ __forceinline__ void keep32(T& x) { asm volatile("" : "+r"(x)); }
template <typename T> __device__ __forceinline__ void keep64(T& x) { asm volatile("" : "+l"(x)); }
#define ACC16(d) "+f"(d[0]), "+f"(d[1]), "+f"(d[2]), "+f"(d[3]), "+f"(d[4]), "+f"(d[5]), "+f"(d[6]), "+f"(d[7]), \
                 "+f"(d[8]), "+f"(d[9]), "+f"(d[10]), "+f"(d[11]), "+f"(d[12]), "+f"(d[13]), "+f"(d[14]), "+f"(d[15])
#define OUT16(d) "=f"(d[0]), "=f"(d[1]), "=f"(d[2]), "=f"(d[3]), "=f"(d[4]), "=f"(d[5]), "=f"(d[6]), "=f"(d[7]), \
                 "=f"(d[8]), "=f"(d[9]), "=f"(d[10]), "=f"(d[11]), "=f"(d[12]), "=f"(d[13]), "=f"(d[14]), "=f"(d[15])
template <int ACC> __device__ __forceinline__ void wg_rs32(float* d, const uint32_t* a, uint64_t db) {
  if (ACC == 2)
    asm volatile("wgmma.mma_async.sync.aligned.m64n32k16.f32.bf16.bf16 "
                 "{%0,%1,%2,%3,%4,%5,%6,%7,%8,%9,%10,%11,%12,%13,%14,%15}, {%16,%17,%18,%19}, %20, 0, 1, 1, 0;"
                 : ACC16(d) : "r"(a[0]), "r"(a[1]), "r"(a[2]), "r"(a[3]), "l"(db));
  else if (ACC)
    asm volatile("wgmma.mma_async.sync.aligned.m64n32k16.f32.bf16.bf16 "
                 "{%0,%1,%2,%3,%4,%5,%6,%7,%8,%9,%10,%11,%12,%13,%14,%15}, {%16,%17,%18,%19}, %20, 1, 1, 1, 0;"
                 : ACC16(d) : "r"(a[0]), "r"(a[1]), "r"(a[2]), "r"(a[3]), "l"(db));
  else
    asm volatile("wgmma.mma_async.sync.aligned.m64n32k16.f32.bf16.bf16 "
                 "{%0,%1,%2,%3,%4,%5,%6,%7,%8,%9,%10,%11,%12,%13,%14,%15}, {%16,%17,%18,%19}, %20, 0, 1, 1, 0;"
                 : OUT16(d) : "r"(a[0]), "r"(a[1]), "r"(a[2]), "r"(a[3]), "l"(db));
}
__device__ __forceinline__ void acc_fence16(float* d) { asm volatile("" : ACC16(d)::"memory"); }
__device__ __forceinline__ void wg_ss32(float* d, uint64_t da, uint64_t db) {
  asm volatile("wgmma.mma_async.sync.aligned.m64n32k16.f32.bf16.bf16 "
               "{%0,%1,%2,%3,%4,%5,%6,%7,%8,%9,%10,%11,%12,%13,%14,%15}, %16, %17, 1, 1, 1, 1, 0;"
               : ACC16(d) : "l"(da), "l"(db));
}
__device__ __forceinline__ void wg_ss32z(float* d, uint64_t da, uint64_t db) {
  asm volatile("wgmma.mma_async.sync.aligned.m64n32k16.f32.bf16.bf16 "
               "{%0,%1,%2,%3,%4,%5,%6,%7,%8,%9,%10,%11,%12,%13,%14,%15}, %16, %17, 0, 1, 1, 1, 0;"
               : OUT16(d) : "l"(da), "l"(db));
}

#define STAMP(i)

__device__ __forceinline__ void wgmma_m64n128_ss_tb(float* d, uint64_t da, uint64_t db) {
  asm volatile(
      "wgmma.mma_async.sync.aligned.m64n128k16.f32.bf16.bf16 "
      "{%0,%1,%2,%3,%4,%5,%6,%7,%8,%9,%10,%11,%12,%13,%14,%15,%16,%17,%18,%19,%20,%21,%22,%23,%24,%25,%26,%27,%28,%29,%30,%31,"
      "%32,%33,%34,%35,%36,%37,%38,%39,%40,%41,%42,%43,%44,%45,%46,%47,%48,%49,%50,%51,%52,%53,%54,%55,%56,%57,%58,%59,%60,%61,%62,%63},"
      "%64,%65,1,1,1,0,1;"
      : "+f"(d[0]), "+f"(d[1]), "+f"(d[2]), "+f"(d[3]), "+f"(d[4]), "+f"(d[5]), "+f"(d[6]), "+f"(d[7]), "+f"(d[8]), "+f"(d[9]),
        "+f"(d[10]), "+f"(d[11]), "+f"(d[12]), "+f"(d[13]), "+f"(d[14]), "+f"(d[15]), "+f"(d[16]), "+f"(d[17]), "+f"(d[18]), "+f"(d[19]),
        "+f"(d[20]), "+f"(d[21]), "+f"(d[22]), "+f"(d[23]), "+f"(d[24]), "+f"(d[25]), "+f"(d[26]), "+f"(d[27]), "+f"(d[28]), "+f"(d[29]),
        "+f"(d[30]), "+f"(d[31]), "+f"(d[32]), "+f"(d[33]), "+f"(d[34]), "+f"(d[35]), "+f"(d[36]), "+f"(d[37]), "+f"(d[38]), "+f"(d[39]),
        "+f"(d[40]), "+f"(d[41]), "+f"(d[42]), "+f"(d[43]), "+f"(d[44]), "+f"(d[45]), "+f"(d[46]), "+f"(d[47]), "+f"(d[48]), "+f"(d[49]),
        "+f"(d[50]), "+f"(d[51]), "+f"(d[52]), "+f"(d[53]), "+f"(d[54]), "+f"(d[55]), "+f"(d[56]), "+f"(d[57]), "+f"(d[58]), "+f"(d[59]),
        "+f"(d[60]), "+f"(d[61]), "+f"(d[62]), "+f"(d[63])
      : "l"(da), "l"(db));
}

constexpr int G_STAGES = 4;
constexpr int G_STAGE_BYTES = 32768;
constexpr int G_SMEM = G_STAGES * G_STAGE_BYTES + 128;

__global__ void __launch_bounds__(288, 2)
gemm_kernel(const __grid_constant__ CUtensorMap tmA, const __grid_constant__ CUtensorMap tmB0,
            const __grid_constant__ CUtensorMap tmB1, const __grid_constant__ CUtensorMap tmB2,
            const __grid_constant__ CUtensorMap tmC, int nb_per, int kblocks, int c_col0, const int* done) {
  extern __shared__ __align__(1024) uint8_t smem_raw[];
  const uint32_t sb = smem_u32(smem_raw);
  if (sb & 1023) __trap();
  const uint32_t bars = sb + G_STAGES * G_STAGE_BYTES;
  const int tid = threadIdx.x, wg = tid >> 7;
  asm volatile("griddepcontrol.launch_dependents;" ::: "memory");
  uint32_t rank; asm("mov.u32 %0, %%cluster_ctarank;" : "=r"(rank));
  const int nt = blockIdx.x, mt = blockIdx.y;
  const int bsel = nt / nb_per, n0 = (nt - bsel * nb_per) * 128;
  const CUtensorMap* tb = bsel == 0 ? &tmB0 : (bsel == 1 ? &tmB1 : &tmB2);
  if (tid == 256) {
    for (int i = 0; i < G_STAGES; i++) { mbar_init(bars + i * 8, 1); mbar_init(bars + (G_STAGES + i) * 8, 4); }
    asm volatile("fence.mbarrier_init.release.cluster;" ::: "memory");
    asm volatile("fence.proxy.async;" ::: "memory");
    for (int kb = 0; kb < G_STAGES; kb++) {
      const uint32_t b = sb + kb * G_STAGE_BYTES + 16384, fb = bars + kb * 8;
      mbar_expect_tx(fb, G_STAGE_BYTES);
      tma2d(b, tb, n0, kb * 64, fb);
      tma2d(b + 8192, tb, n0 + 64, kb * 64, fb);
    }
    for (int i = 0; i < (1 << 22); i++) {
      int v; asm volatile("ld.acquire.gpu.global.s32 %0, [%1];" : "=r"(v) : "l"(done) : "memory");
      if (v == 255) break;
    }
    asm volatile("fence.proxy.async;" ::: "memory");
  }
  __syncwarp();
  cluster_sync();
  if (wg == 2) {
    if (tid == 256) {
      STAMP(3);
      for (int kb = 0; kb < kblocks; kb++) {
        const int st = kb % G_STAGES, ph = (kb / G_STAGES) & 1;
        const uint32_t a = sb + st * G_STAGE_BYTES, b = a + 16384, fb = bars + st * 8;
        if (kb >= G_STAGES) { mbar_wait(bars + (G_STAGES + st) * 8, ph ^ 1); mbar_expect_tx(fb, G_STAGE_BYTES); }
        tma2d_mc(a + rank * 8192, &tmA, kb * 64, mt * 128 + rank * 64, fb, (uint16_t)3);
        if (kb >= G_STAGES) { tma2d(b, tb, n0, kb * 64, fb); tma2d(b + 8192, tb, n0 + 64, kb * 64, fb); }
      }
    }
  } else {
    const int cw = wg;
    float acc[64];
#pragma unroll
    for (int i = 0; i < 64; i++) acc[i] = 0.f;
    for (int kb = 0; kb < kblocks; kb++) {
      const int st = kb % G_STAGES, ph = (kb / G_STAGES) & 1;
      mbar_wait(bars + st * 8, ph);
      const uint32_t a = sb + st * G_STAGE_BYTES + cw * 8192, b = sb + st * G_STAGE_BYTES + 16384;
      const uint64_t da = mk_desc(a, 16, 1024), db = mk_desc(b, 8192, 1024);
      WG_FENCE();
#pragma unroll
      for (int k = 0; k < 4; k++) wgmma_m64n128_ss_tb(acc, da + k * 2, db + k * 128);
      WG_COMMIT();
      WG_WAIT(0);
      if (kb + G_STAGES < kblocks && (tid & 127) < 2) mbar_arrive_cluster(mapa(bars + (G_STAGES + st) * 8, tid & 1));
    }
    WG_WAIT(0);
    bar_sync(1, 256);
    const int w4 = (tid >> 5) & 3, lane = tid & 31;
    const uint32_t cbuf = sb + cw * 16384;
    const int row = w4 * 16 + (lane & 7) + ((lane >> 3) & 1) * 8;
#pragma unroll
    for (int j = 0; j < 8; j++) {
      const int chunk = (j & 3) * 2 + (lane >> 4);
      const uint32_t ad = cbuf + (j >> 2) * 8192 + row * 128 + ((chunk ^ (row & 7)) << 4);
      stsm4(ad, pack_bf16(acc[j * 8 + 0], acc[j * 8 + 1]), pack_bf16(acc[j * 8 + 2], acc[j * 8 + 3]),
            pack_bf16(acc[j * 8 + 4], acc[j * 8 + 5]), pack_bf16(acc[j * 8 + 6], acc[j * 8 + 7]));
    }
    asm volatile("fence.proxy.async.shared::cta;" ::: "memory");
    bar_sync(2 + cw, 128);
    if ((tid & 127) == 0) {
      tma2d_store(&tmC, cbuf, c_col0 + nt * 128, mt * 128 + cw * 64);
      tma2d_store(&tmC, cbuf + 8192, c_col0 + nt * 128 + 64, mt * 128 + cw * 64);
      asm volatile("cp.async.bulk.commit_group; cp.async.bulk.wait_group 0;" ::: "memory");
    }
  }
  __syncwarp();
  cluster_sync();
  if (tid == 0) STAMP(4);
  if (nt == 0 && mt == 0) asm volatile("griddepcontrol.wait;" ::: "memory");
}

__host__ __device__ constexpr uint32_t wpage(int L) {
  return (uint32_t)(((L & 1) << 18) | (((L >> 1) & 1) << 20) | (((L >> 2) & 1) << 13) | (((L >> 3) & 1) << 16) | (((L >> 4) & 1) << 17) |
                    (((L >> 5) & 1) << 19) | ((((L >> 2) ^ (L >> 3) ^ (L >> 4) ^ (L >> 5)) & 1) << 12));
}
constexpr int L_MEM = 0;
constexpr int L_U = 4;
constexpr int L_VM = 20;
constexpr int L_FLAG = 52;
constexpr int L_PROBE = 60;
constexpr int VX0 = 32768;
constexpr int EX_K = 4096, EX_CTA = 9216, EX_BYTES = 2 * EX_CTA;
struct Rings {
  uint32_t side[64];
  uint4 ex[4][NH * EX_BYTES / 16];
  int ctr[5][32];
};
__device__ Rings g_rings;
__device__ uint4 g_win[(4 << 20) / 16];
__device__ unsigned g_epoch;
__device__ bf16 g_ux[S_LEN * HD];
constexpr uint32_t TAG = 0x10000u;

constexpr int SB0 = 1024;
#define POLL_LIMIT (1 << 18)

#define TR(i)
#define TRB(i)
#define TRD(c)
#define CNT(i)
#define LOGT(t)
#define ELECT "{.reg .pred p; elect.sync _|p, 0xffffffff; @p "

#define NPRE 2
#define GLA 3
#define CH4 0
#define GFEN 0
#define CHKN 3
#define HN 57
#define H0POS 0
#define LDM lds16v
#define PIN 0
#define H1POS 1
#define QC0 3
#define QC1 9
#define QC2 15
#define QC3 47
#define RESTART 500
#define FIRST 600
#define ALARM 700
#define EXPT 0
#define BACKOFF 200
#define VMPOS 0
#define MEMMC 0
#define CHPOS 1
#define CDEP 1
#define TKN 0
#define XQ 24
#define XS 8
#define BURST 0
#define ATT 1
#define XP 4
template <bool B> struct BoolC { static constexpr bool value = B; };
template <int N> struct IntC { static constexpr int value = N; };
template <typename T> __device__ __forceinline__ T* goff(T* base, uint32_t bytes) {
  return reinterpret_cast<T*>(reinterpret_cast<char*>(base) + bytes);
}
__device__ __forceinline__ char* other(char* p) { return reinterpret_cast<char*>(reinterpret_cast<uintptr_t>(p) ^ 4096); }
__device__ __forceinline__ uint2 ld_tagged8(const void* p) {
  uint2 v;
  asm volatile("{.reg .b64 t; ld.relaxed.gpu.global.b64 t, [%2]; mov.b64 {%0, %1}, t;}" : "=r"(v.x), "=r"(v.y) : "l"(p) : "memory");
  return v;
}
__device__ __forceinline__ uint32_t clk32() { unsigned long long t; asm volatile("mov.u64 %0, %%clock64;" : "=l"(t)::"memory"); return (uint32_t)t; }
__device__ __forceinline__ uint32_t gtime() { unsigned long long t; asm volatile("mov.u64 %0, %%globaltimer;" : "=l"(t)::"memory"); return (uint32_t)t; }
__device__ __forceinline__ uint32_t time_offset() {
  const uint32_t g0 = gtime() * 9;
  uint32_t a = g0 * -8, c0;
#pragma unroll
  for (int i = 0; i < 8; i++) {
    asm volatile("{.reg .u64 t; .reg .u32 l, h; mov.u64 t, %%globaltimer; mov.b64 {l, h}, t; mad.lo.u32 %0, l, 9, %0;}" : "+r"(a)::"memory");
    if (i == 3) c0 = clk32();
  }
  return g0 + (a >> 3) - c0 * 5;
}
__device__ __forceinline__ void spin_until(uint32_t t, uint32_t tk) {
  const uint32_t d = tk - t;
  asm volatile("{.reg .pred p, q; .reg .u32 i, l, h; .reg .u64 c; .reg .s32 x; mov.u32 i, 0;\n"
               "LS: mov.u64 c, %%clock64; mov.b64 {l, h}, c; mad.lo.s32 x, l, 5, %0; add.u32 i, i, 1; setp.lt.u32 q, i, 4096;\n"
               "setp.lt.and.s32 p, x, 0, q; @p bra LS;}" ::"r"(d) : "memory");
}
struct Pace { int u, m, ok, late, s, c; };
__device__ __forceinline__ uint32_t last_u(uint2 f, const char* flags, int s, uint32_t tk) {
  for (int it = 0; __any_sync(~0u, ((f.x - s) | (f.y - s)) & 16); it++) {
    CNT(4);
    if (it) spin_until(clk32() * 5 + BACKOFF * 5, 0);
    f = ld_tagged8(flags);
    if (it > POLL_LIMIT) FAIL(7000 + s);
  }
  const uint32_t now = clk32() * 5 + tk + 65536;
  return now - __reduce_min_sync(~0u, min(now - f.x, now - f.y));
}
__device__ __forceinline__ uint32_t time_u(uint32_t tm, int s, const Pace& d) { return tm + d.u + (s < 3 ? FIRST * 5 : 0); }
__device__ __forceinline__ uint32_t next_mem(uint32_t tm, uint32_t su, int s, const Pace& d) {
  const uint32_t tu = time_u(tm, s, d);
  return ((int)(su + d.ok - tu) > 0 || s == 0 ? su + d.late : tu) + d.m + (s < 3 ? FIRST * 5 : 0);
}
__device__ __forceinline__ const char* flag_ptr(const char* G, uint32_t near, uint32_t t16) {
  keep32(t16);
  return reinterpret_cast<const char*>(reinterpret_cast<uintptr_t>(G + (wpage(L_FLAG) ^ near)) | ((t16 >> 1) & 0xF8));
}
template <int CS> __device__ __forceinline__ void arrive_all(uint32_t t16, uint32_t off) {
  keep32(t16);
  const uint32_t l = (t16 >> 4) & 31;
  if (l < CS) mbar_arrive_cluster(mapa(SB0 + off, l));
  __syncwarp();
}
template <int N> __device__ __forceinline__ uint32_t idle(uint32_t z) {
#pragma unroll
  for (int i = 0; i < N; i++) asm volatile("mad.lo.u32 %0, %0, %0, %0;" : "+r"(z));
  return z;
}
__device__ __forceinline__ uint32_t junk() { uint32_t x; asm volatile("" : "=r"(x)); return x; }
__device__ __forceinline__ float rcp_fast(float x) { float y; asm("rcp.approx.ftz.f32 %0, %1;" : "=f"(y) : "f"(x)); return y; }
__device__ __forceinline__ void mma_z(float* d, uint32_t a0, uint32_t a1, uint32_t a2, uint32_t a3, uint32_t b0, uint32_t b1) {
  asm volatile("mma.sync.aligned.m16n8k16.row.col.f32.bf16.bf16.f32 {%0,%1,%2,%3}, {%4,%5,%6,%7}, {%8,%9}, {%10,%10,%10,%10};"
               : "=f"(d[0]), "=f"(d[1]), "=f"(d[2]), "=f"(d[3])
               : "r"(a0), "r"(a1), "r"(a2), "r"(a3), "r"(b0), "r"(b1), "f"(0.f));
}
__device__ __forceinline__ void mma1688z(float* d, uint32_t a0, uint32_t a1, uint32_t b0) {
  asm volatile("mma.sync.aligned.m16n8k8.row.col.f32.bf16.bf16.f32 {%0,%1,%2,%3}, {%4,%5}, {%6}, {%7,%7,%7,%7};"
               : "=f"(d[0]), "=f"(d[1]), "=f"(d[2]), "=f"(d[3]) : "r"(a0), "r"(a1), "r"(b0), "f"(0.f));
}
#define MMA_W(d, o, b0, b1) mma16816(d, w[o], w[(o) + 1], w[(o) + 2], w[(o) + 3], b0, b1)
#define MMA_X(d, x, b0, b1) mma16816(d, (x)[0], (x)[1], (x)[2], (x)[3], b0, b1)
#define MMA_XZ(d, x, b0, b1) mma_z(d, (x)[0], (x)[1], (x)[2], (x)[3], b0, b1)
__device__ __forceinline__ void ldw(uint32_t* x, uint32_t a) { ldsm4t(x[0], x[1], x[2], x[3], a); }
__device__ __forceinline__ void ldm(uint32_t* x, uint32_t a) { ldsm4(x[0], x[1], x[2], x[3], a); }
__device__ __forceinline__ void bulk(uint32_t dst, const void* src, uint32_t n, uint32_t bar) {
  asm volatile(ELECT "cp.async.bulk.shared::cluster.global.mbarrier::complete_tx::bytes [%0], [%1], %2, [%3];}" ::"r"(dst), "l"(src), "r"(n), "r"(bar) : "memory");
}
template <uint32_t MASK> __device__ __forceinline__ void bulk_mc(uint32_t dst, const void* src, uint32_t n, uint32_t bar) {
  asm volatile(ELECT "cp.async.bulk.shared::cluster.global.mbarrier::complete_tx::bytes.multicast::cluster [%0], [%1], %2, [%3], %4;}"
               ::"r"(dst), "l"(src), "r"(n), "r"(bar), "h"((uint16_t)MASK) : "memory");
}
__device__ __forceinline__ void issue_x(const CUtensorMap* tm, uint32_t dst, uint32_t bar, int seg, int chunk, uint32_t mask) {
  asm volatile(ELECT "cp.async.bulk.tensor.3d.shared::cluster.global.mbarrier::complete_tx::bytes.multicast::cluster [%0], [%1, {%3, %4, %5}], [%2], %6;}"
               ::"r"(dst), "l"(tm), "r"(bar), "r"(0), "r"(seg * SEG), "r"(chunk), "h"((uint16_t)mask) : "memory");
}
__device__ __forceinline__ void expect(uint32_t bar, uint32_t bytes) {
  asm volatile(ELECT "mbarrier.arrive.expect_tx.shared::cta.b64 _, [%0], %1;}" ::"r"(bar), "r"(bytes) : "memory");
}
__device__ __forceinline__ void wait_ft(uint32_t bar, uint32_t par) {
  asm volatile("{.reg .pred p, q; .reg .u32 i; mov.u32 i, 0;\n"
               "LW: add.u32 i, i, 1; setp.lt.u32 q, i, 0x20000;\n"
               "mbarrier.try_wait.parity.shared::cta.b64 p, [%0], %1;\n"
               "not.pred p, p; and.pred q, q, p; @q bra LW;}" ::"r"(bar), "r"(par) : "memory");
}
__device__ __forceinline__ char* ptr64(uint32_t lo, uint32_t hi) { return reinterpret_cast<char*>(((uint64_t)hi << 32) | lo); }
__device__ __forceinline__ uint32_t plo(const void* p) { return (uint32_t)reinterpret_cast<uintptr_t>(p); }
__device__ __forceinline__ uint32_t phi(const void* p) { return (uint32_t)(reinterpret_cast<uintptr_t>(p) >> 32); }
__device__ __forceinline__ uint32_t pack_tag(float lo, float hi, uint32_t tg) {
  return ((__float_as_uint(hi) + (tg ^ TAG)) & 0xFFFE0000u) | pack_bf16(lo, __uint_as_float(tg));
}
__device__ __forceinline__ void st_tagged8(void* p, uint32_t a, uint32_t b) {
  asm volatile("{.reg .b64 t; mov.b64 t, {%1, %2}; st.relaxed.gpu.global.b64 [%0], t;}" ::"l"(p), "r"(a), "r"(b) : "memory");
}
__device__ __forceinline__ void st_tagged8_if(void* p, uint32_t a, uint32_t b, bool c) {
  asm volatile("{.reg .b64 t; .reg .pred q; setp.ne.u32 q, %3, 0; mov.b64 t, {%1, %2}; @q st.relaxed.gpu.global.b64 [%0], t;}" ::"l"(p), "r"(a), "r"(b), "r"((uint32_t)c) : "memory");
}
__device__ __forceinline__ void st_tagged16(void* p, uint4 v) {
  asm volatile("{.reg .b128 t; .reg .b64 a, b; mov.b64 a, {%1, %2}; mov.b64 b, {%3, %4}; mov.b128 t, {a, b}; st.relaxed.gpu.global.b128 [%0], t;}"
               ::"l"(p), "r"(v.x), "r"(v.y), "r"(v.z), "r"(v.w) : "memory");
}
__device__ __forceinline__ uint4 ld_tagged16(const void* p) {
  uint4 v;
  asm volatile("{.reg .b128 t; .reg .b64 a, b; ld.relaxed.gpu.global.b128 t, [%4]; mov.b128 {a, b}, t; mov.b64 {%0, %1}, a; mov.b64 {%2, %3}, b;}"
               : "=r"(v.x), "=r"(v.y), "=r"(v.z), "=r"(v.w) : "l"(p) : "memory");
  return v;
}
__device__ __forceinline__ void chk2(uint32_t& c, const uint4& v, uint32_t tg) {
  asm volatile("lop3.b32 %0, %0, %1, %3, 0xF6; lop3.b32 %0, %0, %2, %3, 0xF6;" : "+r"(c) : "r"(v.x), "r"(v.z), "r"(tg));
}
__device__ __forceinline__ void sched_fence(uint32_t zero, int n) {
  asm volatile("{.reg .pred p; setp.eq.u32 p, %0, %1; @p exit;}" ::"r"(zero), "r"(n + 1001) : "memory");
}
__device__ __forceinline__ void pin(uint64_t& x, uint32_t zero) {
  asm volatile("{.reg .pred p; setp.ne.u32 p, %1, 0; @p mov.u64 %0, %%clock64;}" : "+l"(x) : "r"(zero) : "memory");
}
__device__ __forceinline__ void landed(uint32_t y) {
  asm volatile("{.reg .pred p; setp.ne.u32 p, %0, 0; vote.sync.any.pred p, p, 0xffffffff; @p exit;}" ::"r"(y) : "memory");
}
__device__ __forceinline__ uint64_t cdesc(uint32_t v, int off) {
  const uint32_t lo = v + (uint32_t)(((SB0 + off) >> 4) | (1 << 16));
  return ((uint64_t)0x40000040u << 32) | lo;
}
__device__ __forceinline__ uint64_t ndesc(uint32_t v, int off, int kstr, int mstr) {
  const uint32_t lo = v + (uint32_t)(((SB0 + off) >> 4) | ((kstr >> 4) << 16));
  return ((uint64_t)(mstr >> 4) << 32) | lo;
}
__device__ __forceinline__ constexpr int xk(int k) { return (k >> 2) * 4096 + (k & 3) * 32; }
constexpr uint32_t ONE2 = 0x3F803F80u;
constexpr float SCL = 0.08838834764831845f * 1.4426950408889634f;
__device__ __forceinline__ void exp10v(float* sc) {
  float ml = fmaxf(fmaxf(fmaxf(sc[0], sc[1]), fmaxf(sc[2], sc[3])), fmaxf(fmaxf(sc[4], sc[5]), fmaxf(sc[6], sc[7])));
  ml = fmaxf(ml, fmaxf(sc[8], sc[9]));
  const float m1 = __shfl_xor_sync(~0u, ml, 1), m2 = __shfl_xor_sync(~0u, ml, 2), m3 = __shfl_xor_sync(~0u, ml, 3);
  const float mo = fmaxf(fmaxf(ml, m1), fmaxf(m2, m3));
#pragma unroll
  for (int i = 0; i < 10; i++) sc[i] = ex2(sc[i] - mo);
}
#define UNI(x) __reduce_max_sync(~0u, (uint32_t)(x))
#define OPQ(x) __shfl_sync(~0u, (uint32_t)(x), lane)
#define BASES() uint32_t t16 = t16_; keep32(t16); const uint32_t l16 = t16 + wofs; (void)l16
__device__ __forceinline__ uint32_t probe_near(char* G, int id) {
  unsigned* p0 = reinterpret_cast<unsigned*>(G + wpage(L_PROBE + (id >> 5)) + (id & 31) * 128);
  unsigned best[2] = {~0u, ~0u}, x = 0;
  for (int i = 0; i < 12; i++) {
    const unsigned t0 = clock();
    x = atomicExch(reinterpret_cast<unsigned*>(reinterpret_cast<uintptr_t>(p0) ^ ((i & 1) << 12)) + (x >> 31), (unsigned)i);
    const unsigned t1 = clock() + (x >> 31);
    best[i & 1] = min(best[i & 1], t1 - t0);
  }
  return best[1] < best[0] ? 4096u : 0u;
}
__device__ __forceinline__ void start_barrier() {
  __threadfence();
  const unsigned target = (atomicAdd(&g_epoch, 1u) & ~127u) + 128u;
  for (int i = 0;; i++) {
    unsigned v; asm volatile("ld.acquire.gpu.global.u32 %0, [%1];" : "=r"(v) : "l"(&g_epoch) : "memory");
    if ((int)(v - target) >= 0) break;
    if (i > (1 << 20)) FAIL(9000);
  }
  asm volatile("fence.proxy.async;" ::: "memory");
}

template <int CS> __device__ __forceinline__ void fetch_mem_mc(uint32_t dst, const char* G, uint32_t off, int rank, uint32_t bar) {
  constexpr int PB = CS == 8 ? 2048 : 4096;
#pragma unroll
  for (int i = 0; i < 16384 / PB / CS; i++) {
    const uint32_t o = (rank * (16384 / PB / CS) + i) * PB;
    bulk_mc<(1u << CS) - 1>(dst + o, G + (off + ((o & 4096) << 6) + ((o & 8192) << 7) + (o & 4095)), PB, bar);
  }
}
template <int wg, int MEM, bool PRE, typename GV, typename W, typename F>
__device__ __forceinline__ void gemv_mem(GV& gv, const uint32_t* w, int s, uint32_t t16_, uint32_t wofs, uint32_t near, char* G, W wsa,
                                         uint32_t bar, uint32_t zero, uint32_t trc, F hook) {
  const uint32_t tg = (s & 1) << 16;
#pragma unroll 1
  for (;;) {
    BASES();
    const uint32_t mb = l16 + MEM + wg * 8192;
    if (PRE) landed(gv.prefetch(lds4(wsa(t16))) & zero);
    TR(14);
    wait_ft(bar, s & 1);
    TR(0);
    gv.first(mb);
    gv.c = 0;
    gv.tg = tg; gv.z0 = zero;
    bool bad;
    gv.template run<0, 16>(w, mb, [&](auto nc) __attribute__((always_inline)) {
      if (decltype(nc)::value == GV::CV) bad = __any_sync(~0u, gv.c & (s ? TAG : 0));
      hook(nc, bad);
    });
    if (__builtin_expect(!bad, 1)) break;
    CNT(MEM == 0x28000 ? 0 : 2);
    uint4 v[4];
    const char* src = G + (near + (wg << 20) + ((t16 - SB0) & 0x7F0));
    for (int it = 0;; it++) {
      uint32_t c = 0;
#pragma unroll
      for (int i = 0; i < 4; i++) v[i] = ld_tagged16(src + (i & 1) * 2048 + (i >> 1) * (1 << 18));
#pragma unroll
      for (int i = 0; i < 4; i++) chk2(c, v[i], tg);
      if (!__any_sync(~0u, c & TAG)) break;
      if (it > POLL_LIMIT) FAIL(2000);
    }
    bar_sync(1 + wg, 128);
#pragma unroll
    for (int i = 0; i < 4; i++) sts16(t16 + (MEM + wg * 6144) + i * 2048, v[i]);
    if (!PRE) landed(gv.prefetch(lds4(wsa(t16))) & zero);
    bar_sync(1 + wg, 128);
  }
}

constexpr int A_WS = 0;
constexpr int A_X = 65536;
constexpr int A_H1 = A_X + 32768;
constexpr int A_MEM = A_X + 98304;
constexpr int A_QX = A_MEM + 16384, A_KX = A_QX + EX_K, A_QM = A_QX + EX_CTA;
constexpr int A_SB = A_QM + 1024;
constexpr int A_BARS = A_X + 131072;
constexpr int A_TRC = A_BARS + 256;
constexpr int A_TAB = A_BARS + 1024;
constexpr int A_PQ = A_TAB + 16384;
constexpr int A_PS = A_PQ + 8192;
constexpr int A_SMEM = A_PS + 4096;
constexpr int B_RES = 64, B_PAIR = 72, B_H0 = 80, B_H1 = 88  , B_M = 104, B_XE = 112, B_EXD = 120, B_HO = 0  , B_T = 128  , B_NEAR = 136, B_TK = 140;

template <int NP> struct GemvQK {
  float a[4], b[4], a2[4], b2[4];
  uint4 m[16];
  uint32_t pp[4][16], ws, z0, c, tg;
  static __device__ __forceinline__ constexpr int blk(int n) {
    return NP == 2 ? (n < 2 ? 12 + n : n == 7 ? 14 : n == 13 ? 15 : n - 2 - (n > 7) - (n > 13)) : (n < 3 ? 12 + n : n == 10 ? 15 : n - 3 - (n > 10));
  }
  static __device__ __forceinline__ constexpr int lm(int n) { return NP == 3 && n < 1 ? n + 3 : NP == 3 && n < 2 ? n + 4 : n + 1 + GLA > 16 ? 16 : n + 1 + GLA; }
  static __device__ __forceinline__ constexpr int lw(int n) {
    return NP == 2 ? (n >= 2 && n <= 5 ? 6 + n : n >= 8 && n <= 11 ? 4 + n : 0) : (n >= 3 && n <= 8 && n != 5 && n != 7 ? 9 + n - (n > 5) - (n > 7) : 0);
  }
  template <int J0 = 0, int J1 = NP * 4> __device__ __forceinline__ uint32_t prefetch(uint32_t a) {
    ws = a;
    uint32_t y = ~0u;
#pragma unroll
    for (int j = J0; j < J1; j++) { ldw(pp[j >> 2] + (j & 3) * 4, ws + (j >> 1) * 2048 + (j & 1) * 16384); y &= pp[j >> 2][(j & 3) * 4]; }
    return y;
  }
  __device__ __forceinline__ void first(uint32_t mb) {
#pragma unroll
    for (int n = 0; n < lm(-1); n++) m[n] = lds16v(mb + blk(n) * 512);
  }
  template <int N, int END, typename F> __device__ __forceinline__ void run(const uint32_t* w, uint32_t mb, F hook) {
    if constexpr (N < END) {
      constexpr int bi = blk(N), o2 = bi >= 12 ? 8 : 4, j = lw(N);
      const uint32_t* pa = bi >= 12 ? pp[bi >= 12 ? bi - 12 : 0] : w + bi * 8;
      const uint32_t* pb = bi >= 12 ? pa + 4 : pa + 96;
      if (N == 0) MMA_XZ(a, pa, m[N].x, m[N].y); else MMA_X(a, pa, m[N].x, m[N].y);
      if (j) ldw(pp[j >> 2] + (j & 3) * 4, ws + (j >> 1) * 2048 + (j & 1) * 16384);
      hook(IntC<4 * N>());
      if (N == 0) MMA_XZ(b, pb, m[N].x, m[N].y); else MMA_X(b, pb, m[N].x, m[N].y);
      hook(IntC<4 * N + 1>());
      if (N == 0) MMA_XZ(a2, pa + o2, m[N].z, m[N].w); else MMA_X(a2, pa + o2, m[N].z, m[N].w);
      if (lm(N) - lm(N - 1) == 2) m[lm(N) - 2] = lds16v(mb + blk(lm(N) - 2) * 512);
      hook(IntC<4 * N + 2>());
      if (N == 0) MMA_XZ(b2, pb + o2, m[N].z, m[N].w); else MMA_X(b2, pb + o2, m[N].z, m[N].w);
      if (N < 13) c |= m[N].x ^ tg;
      if (N == 13) c |= (m[13].x ^ tg) | (m[14].x ^ tg) | (m[15].x ^ tg);
      if (lm(N) > lm(N - 1)) m[lm(N) - 1] = lds16v((CDEP ? mb | (c & z0) : mb) + blk(lm(N) - 1) * 512);
      hook(IntC<4 * N + 3>());
      run<N + 1, END>(w, mb, hook);
    }
  }
  static constexpr int CV = 55;
};

#define TKA (bars + B_TK)
template <int CS>
__device__ __forceinline__ void qk_body(const CUtensorMap& tmWq, const CUtensorMap& tmWk, const CUtensorMap& tmX,
                                        char* __restrict__ G, const Pace d, int zero, int block) {
  extern __shared__ __align__(1024) uint8_t smem_raw[];
  const uint32_t sb = smem_u32(smem_raw);
  if ((sb & 0x3FFFF) != SB0) __trap();
  asm volatile("griddepcontrol.launch_dependents;" ::: "memory");
  const int tid = threadIdx.x, t7 = tid & 127, lane = tid & 31;
  const int warp = UNI(tid >> 5), wg = warp >> 2, w4 = warp & 3;
  const uint32_t wofs = UNI((tid >> 5) * -512);
  const int cta = UNI(block), r = cta & 1, head = cta >> 1, fcol = cta * 64, rank = cta & (CS - 1);
  constexpr uint32_t ALL = (1u << CS) - 1;
  const uint32_t bars = sb + A_BARS;
  const uint32_t trc = UNI(sb + A_TRC + (tid >> 5) * 64); (void)trc;
  if (tid == 0) {
    STAMP(0);
    for (int i = 0; i < 32; i++) if ((i & 24) != 16) mbar_init(bars + i * 8, i * 8 == B_XE ? CS : 1);
    asm volatile("fence.mbarrier_init.release.cluster;" ::: "memory");
  }
  const uint32_t gu = wpage(L_U + (cta >> 2)) + (cta & 3) * 1024;
  if (tid < 128) *reinterpret_cast<uint4*>(G + ((gu + (tid & 63) * 16) ^ ((tid & 64) << 6))) = make_uint4(0, 0, 0, 0);
  if (tid < 2) *reinterpret_cast<uint32_t*>(G + (wpage(L_FLAG) ^ (tid << 12)) + cta * 4) = 31;
  __syncthreads();
  const uint32_t stg = sb + A_X + wg * 65536;
  const uint32_t sbar = bars + wg * 32;
  const int lk = (lane & 7) + ((lane >> 4) << 3);
  const uint32_t wt_off = lk * 128 + (((((tid >> 4) & 6) + ((lane >> 3) & 1)) ^ (lk & 7)) << 4);
  const int g = lane >> 2, c = lane & 3;
  if (t7 == 0) {
    for (int i = 0; i < 4; i++) {
      mbar_expect_tx(sbar + i * 8, 16384);
      tma2d_ef(stg + i * 16384, i < 3 ? &tmWk : &tmWq, fcol, wg * 512 + (i % 3) * 128, sbar + i * 8);
    }
    if (wg == 0) {
      mbar_expect_tx(bars + B_RES, 65536);
      for (int i = 0; i < 4; i++) tma2d_ef(sb + A_WS + i * 16384, (i & 1) ? &tmWq : &tmWk, fcol, (i >> 1) * 512 + 384, bars + B_RES);
    }
  }
  if (tid == 64) {
    const uint32_t n = probe_near(G, cta);
    sts4f(bars + B_NEAR, __uint_as_float(n));
    g_rings.side[cta] = n;
    start_barrier();
  }
  __syncwarp();
  uint32_t w[192];
  const uint32_t t16_ = OPQ(sb + tid * 16);
#pragma unroll
  for (int i = 0; i < 6; i++) {
    mbar_wait(sbar + (i & 3) * 8, i >> 2);
#pragma unroll
    for (int j = 0; j < 8; j++) ldw(w + (i * 8 + j) * 4, stg + (i & 3) * 16384 + j * 2048 + wt_off);
    if (i == 1) {
      bar_sync(1 + wg, 128);
      if (t7 == 0)
        for (int i2 = 4; i2 < 6; i2++) {
          mbar_expect_tx(sbar + (i2 & 3) * 8, 16384);
          tma2d_ef(stg + (i2 & 3) * 16384, &tmWq, fcol, wg * 512 + (i2 - 3) * 128, sbar + (i2 & 3) * 8);
        }
    }
  }
  mbar_wait(bars + B_RES, 0);
  cluster_sync();
  if (tid == 0) STAMP(1);
  const uint32_t near = UNI(lds4(bars + B_NEAR));
  auto fetch_x = [&](uint32_t buf, uint32_t bar, int n, int h) __attribute__((always_inline)) {
    if ((EXPT & (4 << h)) && n > 1) asm volatile(ELECT "mbarrier.complete_tx.shared::cta.b64 [%0], 32768;}" ::"r"(bars + bar) : "memory");
    else issue_x(&tmX, sb + buf + rank * (32768 / CS), bars + bar, n, h * 8 + rank * (8 / CS), ALL);
  };
  if (warp == 7) {
    expect(bars + B_H0, 32768); expect(bars + B_H1, 32768); expect(bars + B_H1 + 8, 32768);
    fetch_x(A_H1, B_H1, 0, 1); fetch_x(A_X, B_H0, 0, 0); fetch_x(A_H1 + 32768, B_H1 + 8, 1, 1);
    expect(bars + B_PAIR, 1280);
    expect(bars + B_M, 16384);
  }
  const uint32_t rdelta = UNI(mapa(sb, rank ^ 1) - sb);
  {
    const int w4 = (tid >> 5) & 3, wg = tid >> 7;
    const int ch = 2 * w4 + ((lane >> 3) & 1);
    const uint32_t qst = sb + (lane & 7) * 16 + ((lane >> 4) ? A_QM + (w4 >> 1) * 512 + (ch & 1) * 256 + (w4 & 1) * 128 : A_KX + ch * 640 + 512);
    const uint32_t fst = sb + (lane & 7) * 16 + (wg ? A_QX + w4 * 1024 + (lane >> 3) * 128 : A_KX + ch * 640 + (lane >> 4) * 128);
    const uint32_t kba = sb + (lane & 7) * 16 + A_KX + (lane >> 3) * 640 + (tid >> 5) * 128;
    const uint32_t sbo = sb + A_SB + lane * 16 + (w4 & 1) * 8 + (tid >> 6) * 512;
    const uint32_t sbr = sb + rdelta + A_SB + 1536 + tid * 8;
    const char* vmp = G + ((wpage(L_VM + head) ^ near) + r * 2048 + t7 * 8);
    const char* up = G + ((gu ^ near ^ 4096) + (w4 >> 1) * 512 + g * 64 + (w4 & 1) * 32 + c * 8);
    const char* vxp = G + ((wpage(cta) ^ near) + VX0 + w4 * 1024 + lane * 16);
    sts16(t16_ + A_TAB, make_uint4(sbr, bars + B_PAIR + rdelta, sbo, qst));
    sts16(t16_ + A_TAB + 4096, make_uint4(plo(vmp), phi(vmp), plo(vxp), phi(vxp)));
    sts16(t16_ + A_TAB + 8192, make_uint4(kba, 0, fst, sb + A_WS + wg * 32768 + wt_off));
    sts16(t16_ + A_TAB + 12288, make_uint4(plo(up), phi(up), plo(up) ^ 4096, phi(up)));
    if (tid < 32) sts4f(t16_ + A_SB + 1032, __uint_as_float(sb + A_SB + 1536 + lane * 8));
    if (tid == 0) sts4f(bars + B_T, 0.f);
  }
  __syncthreads();
  auto fetch_mem = [&](uint32_t slot) __attribute__((always_inline)) {
    if (CS == 2 && !MEMMC) {
#pragma unroll
      for (int p = 0; p < 4; p++) bulk(sb + A_MEM + p * 4096, G + (near + slot) + wpage(L_MEM + p), 4096, bars + B_M);
    } else fetch_mem_mc<CS>(sb + A_MEM, G, near + slot, rank, bars + B_M);
  };
  const uint32_t hob = UNI(sb + A_BARS + 192 + ((tid >> 2) & 24));
  auto proj = [&](int s, auto& gv, auto wg_c, auto gate, auto mid, auto between, auto mid2) __attribute__((always_inline)) {
    constexpr int wg = decltype(wg_c)::value, XB = wg ? A_H1 : A_X;
    uint32_t z = wg ? ((s + 1) & 1) * 2048 : s & wofs & zero;
    float d[16];
    uint32_t f[8];
    auto pass = [&](auto m_c, auto first_c) __attribute__((always_inline)) {
      constexpr int m = decltype(m_c)::value;
      constexpr bool first = decltype(first_c)::value;
      if (first && (wg == 0 || BURST == 0)) gate();
      WG_FENCE();
#pragma unroll
      for (int k = 0; k < XQ; k++) {
        if (k == 0) wg_rs32<0>(d, w + m * 96, cdesc(z, XB)); else wg_rs32<1>(d, w + m * 96 + 4 * k, cdesc(z, XB + xk(k)));
        if (first && wg == 1 && k == BURST - 1) { WG_COMMIT(); gate(); WG_FENCE(); }
      }
#pragma unroll
      for (int j = 2; j < XS; j++) wg_ss32(d, cdesc(0, A_WS + wg * 32768 + m * 16384 + j * 2048), cdesc(z, XB + xk(24 + j)));
      if (first && wg == 0) WG_FENCE();
#pragma unroll
      for (int j = 0; j < 2; j++) wg_rs32<1>(d, gv.pp[0] + j * 8 + m * 4, cdesc(z, XB + xk(24 + j)));
      WG_COMMIT();
    };
    gv.template prefetch<0, 4>(lds4(t16_ + A_TAB + 8204));
    pass(IntC<1 - wg>(), BoolC<true>());
    TR(8);
    if (wg) mid();
    z = wg ? UNI(z | zero) : 0;
    WG_WAIT(0);
    TR(9);
    acc_fence16(d);
    sts16(t16_ + A_PQ, make_uint4(pack_bf16(d[0], d[1]), pack_bf16(d[2], d[3]), pack_bf16(d[4], d[5]), pack_bf16(d[6], d[7])));
    sts16(t16_ + A_PQ + 4096, make_uint4(pack_bf16(d[8], d[9]), pack_bf16(d[10], d[11]), pack_bf16(d[12], d[13]), pack_bf16(d[14], d[15])));
    __syncwarp();
    asm volatile(ELECT "mbarrier.arrive.shared::cta.b64 _, [%0];}" ::"r"(hob + wg * 32) : "memory");
    between();
    pass(IntC<wg>(), BoolC<false>());
    mid2();
    wait_ft(hob + 32 - wg * 32, (s + 1) & 1);
    const uint4 p0 = lds16(t16_ + A_PQ + 2048 - wg * 4096), p1 = lds16(t16_ + A_PQ + 6144 - wg * 4096);
    const uint2 tc = lds8(t16_ + A_TAB + 8200);
    if (ATT) wait_ft(bars + B_EXD, s & 1);
    TR(10);
    WG_WAIT(0);
    TR(11);
    acc_fence16(d);
    const uint32_t p[8] = {p0.x, p0.y, p0.z, p0.w, p1.x, p1.y, p1.z, p1.w};
#pragma unroll
    for (int i = 0; i < 8; i++) f[i] = pack_bf16(d[2 * i] + __uint_as_float(p[i] << 16), d[2 * i + 1] + __uint_as_float(p[i] & 0xFFFF0000u));
    stsm4t(tc.x, f[0], f[1], f[2], f[3]); stsm4t(tc.x + (wg ? 512 : 256), f[4], f[5], f[6], f[7]);
    gv.template prefetch<4>(tc.y);
  };
  auto fetch_h1 = [&](int s) __attribute__((always_inline)) {
    if (w4 == 1 && s + 2 < NSEG) {
      expect(bars + B_H1 + (s & 1) * 8, 32768);
      fetch_x(A_H1 + (s & 1) * 32768, B_H1 + (s & 1) * 8, s + 2, 1);
    }
  };
  auto send_qk = [&](int s) __attribute__((always_inline)) {
    asm volatile(ELECT "cp.async.bulk.global.shared::cta.bulk_group [%0], [%1], %2;}"
                 ::"l"(reinterpret_cast<char*>(g_rings.ex[s & 3]) + cta * EX_CTA), "r"(sb + A_QX), "r"(EX_CTA) : "memory");
    asm volatile("cp.async.bulk.commit_group;" ::: "memory");
  };
  auto sent_qk = [&]() __attribute__((always_inline)) {
    asm volatile("cp.async.bulk.wait_group 0;" ::: "memory");
    __syncwarp();
    asm volatile(ELECT "mbarrier.arrive.shared::cta.b64 _, [%0];}" ::"r"(bars + B_EXD) : "memory");
  };
  auto chores = [&](int s) __attribute__((always_inline)) {
    if (w4 == 1 || w4 == 2) {
      if (s) spin_until(time_u(lds4(bars + B_T + (s & 1) * 4), s, d) + d.c, lds4(bars + B_TK));
    }
    if (ATT && w4 == 2 && !(EXPT & 32)) send_qk(s);
    fetch_h1(s);
  };
  if (warp == 7) fetch_mem(16384);
  mbar_wait(bars + B_H1, 0);
  auto scores = [&](const uint32_t* kb, uint32_t l16, const uint4& ta, auto shadow) __attribute__((always_inline)) {
    float sp[4][4];
    uint32_t a[8];
    ldm(a, l16 + A_QM); ldm(a + 4, l16 + A_QM + 512);
    shadow();
#pragma unroll
    for (int i = 0; i < 4; i++) MMA_XZ(sp[i], a + (i >> 1) * 4, kb[2 * i], kb[2 * i + 1]);
    const float x = ((sp[0][0] + sp[1][2]) + sp[2][0]) + sp[3][2];
    const float y = ((sp[0][1] + sp[1][3]) + sp[2][1]) + sp[3][3];
    st_async8(ta.x, x, y, ta.y);
    sts8f(ta.z, x, y);
    return __float_as_uint(y) & zero;
  };
  if (wg == 0) {
    GemvQK<2> gv;
    proj(-1, gv, IntC<0>(), [&]() __attribute__((always_inline)) { wait_ft(bars + B_H0, 0); }, []() {}, []() {}, []() {});
#pragma unroll 1
    for (int s = UNI(zero);; s = UNI(s + 1)) {
      uint32_t kb[8], x[4], kba;
      float4 pa, pb;
      uint32_t mbq = t16_;
      keep32(mbq);
      mbq += wofs;
      uint4 ta, tb, v0, v1;
      gemv_mem<0, A_MEM, false>(gv, w, s, t16_, wofs, near, G, [](uint32_t t) { return t + A_TAB + 8204; }, bars + B_M, zero, trc, [&](auto nc, bool bad) __attribute__((always_inline)) {
        constexpr int N = decltype(nc)::value;
        if (N == 49) tb = lds16v(t16_ + A_TAB + 4096);
        if (N == 53) ta = lds16v(t16_ + A_TAB);
        if (N == HN) asm volatile("{.reg .pred p; setp.eq.u32 p, %1, 0; @p bar.sync %0, 64;}" ::"r"(10 + w4), "r"((uint32_t)bad) : "memory");
        if (N == HN + 3) { pa = lds16fv(t16_ + A_PS); pb = lds16fv(t16_ + A_PS + 2048); }
        if (N == 51) kba = lds4v(t16_ + A_TAB + 8192);
        if (N == 61) { ldm(kb, kba); ldm(kb + 4, kba + 2560); }
      });
      const uint32_t l16 = mbq;
      {
        x[0] = pack_bf16((gv.a[0] + pa.x) + gv.a2[0], (gv.a[1] + pa.y) + gv.a2[1]); x[1] = pack_bf16((gv.a[2] + pa.z) + gv.a2[2], (gv.a[3] + pa.w) + gv.a2[3]);
        x[2] = pack_bf16((gv.b[0] + pb.x) + gv.b2[0], (gv.b[1] + pb.y) + gv.b2[1]); x[3] = pack_bf16((gv.b[2] + pb.z) + gv.b2[2], (gv.b[3] + pb.w) + gv.b2[3]);
      }
      stsm4t(ta.w, x[0], x[1], x[2], x[3]);
      TR(1);
      bar_sync(7, 160);
      const char* vxp = ptr64(tb.z + (s & 1) * 16384, tb.w);
      const char* vmp = ptr64(tb.x | scores(kb, l16, ta, [&]() __attribute__((always_inline)) {
        v0 = ld_tagged16(vxp); v1 = ld_tagged16(vxp + 512);
      }), tb.y);
      uint2 va, vb;
      if (VMPOS == 0) { va = ld_tagged8(vmp); vb = ld_tagged8(vmp + 1024); }
      TR(3);
      bar_sync(9, 256);
      float4 p0 = lds16fv(l16 + A_SB), p1 = lds16fv(l16 + A_SB + 512), p2 = lds16fv(l16 + A_SB + 1024);
      const uint4 tu4 = lds16v(t16_ + A_TAB + 12288);
      if (s == NSEG - 1) break;
      const uint32_t l8 = __float_as_uint(p2.z) | (tu4.x & zero);
      p0.x *= SCL; p0.y *= SCL; p0.z *= SCL; p0.w *= SCL; p1.x *= SCL; p1.y *= SCL; p1.z *= SCL; p1.w *= SCL; p2.x *= SCL; p2.y *= SCL;
      if (VMPOS == 1) { vmp = ptr64(plo(vmp) | (__float_as_uint(p2.y) & zero), phi(vmp)); va = ld_tagged8(vmp); vb = ld_tagged8(vmp + 1024); }
      wait_ft(bars + B_PAIR, s & 1);
      TR(4);
      float sc[10];
      {
        const float2 q0 = lds8f(l8), q1 = lds8f(l8 + 256), q2 = lds8f(l8 + 512), q3 = lds8f(l8 + 768), q4 = lds8f(l8 + 1024);
        sc[0] = fmaf(q0.x, SCL, p0.x); sc[1] = fmaf(q0.y, SCL, p0.y); sc[2] = fmaf(q1.x, SCL, p0.z); sc[3] = fmaf(q1.y, SCL, p0.w);
        sc[4] = fmaf(q2.x, SCL, p1.x); sc[5] = fmaf(q2.y, SCL, p1.y); sc[6] = fmaf(q3.x, SCL, p1.z); sc[7] = fmaf(q3.y, SCL, p1.w);
        sc[8] = fmaf(q4.x, SCL, p2.x); sc[9] = fmaf(q4.y, SCL, p2.y);
      }
      exp10v(sc);
      uint32_t p[5];
#pragma unroll
      for (int i = 0; i < 5; i++) p[i] = pack_bf16(sc[2 * i], sc[2 * i + 1]);
      const uint32_t tu = (~s & 1) << 16, tx = (~s & 2) << 15;
      auto pv = [&](bool ok) __attribute__((always_inline)) {
        float o0[4], o1[4], os[4], m0[4], m1[4];
        const uint32_t j0 = junk(), j1 = junk(), j2 = junk(), j3 = junk(), j4 = junk();
        mma_z(os, p[0], j0, p[1], j1, ONE2, ONE2); mma_z(o0, p[0], j0, p[1], j1, v0.x, v0.y); mma_z(o1, p[0], j0, p[1], j1, v1.x, v1.y);
        mma16816(os, p[2], j2, p[3], j3, ONE2, ONE2); mma16816(o0, p[2], j2, p[3], j3, v0.z, v0.w); mma16816(o1, p[2], j2, p[3], j3, v1.z, v1.w);
        mma1688(os, p[4], j4, ONE2);
        mma1688z(m0, p[4], j4, vb.x); mma1688z(m1, p[4], j4, vb.y);
        mma1688(o0, p[4], j4, va.x); mma1688(o1, p[4], j4, va.y);
        const float inv = rcp_fast(os[0]);
        const uint32_t u0 = pack_tag((o0[0] + m0[0]) * inv, (o0[1] + m0[1]) * inv, tu), u1 = pack_bf16((o1[0] + m1[0]) * inv, (o1[1] + m1[1]) * inv);
        st_tagged8_if(ptr64(tu4.x, tu4.y), u0, u1, ok);
        st_tagged8_if(ptr64(tu4.z, tu4.w), u0, u1, ok);
      };
      if (EXPT & 2) { v0.x = tx; v1.x = tx; }
      const bool bad = __any_sync(~0u, ((va.x ^ tu) | (vb.x ^ tu) | (v0.x ^ tx) | (v1.x ^ tx)) & TAG);
      pv(!bad);
      if (__builtin_expect(bad, 0)) {
        CNT(1);
        int it = 0;
        do {
          v0 = ld_tagged16(vxp); v1 = ld_tagged16(vxp + 512);
          va = ld_tagged8(vmp); vb = ld_tagged8(vmp + 1024);
          if (EXPT & 2) { v0.x = tx; v1.x = tx; }
          if (++it > POLL_LIMIT) FAIL(3000 + s);
        } while (__any_sync(~0u, ((va.x ^ tu) | (vb.x ^ tu) | (v0.x ^ tx) | (v1.x ^ tx)) & TAG));
        pv(true);
      }
      bar_arrive(3, 256);
      TR(7);
      proj(s, gv, IntC<0>(), [&]() __attribute__((always_inline)) { wait_ft(bars + B_H0, (s + 1) & 1); TR(5); }, []() {}, []() {}, []() {});
      TRD(cta);
    }
  } else {
    GemvQK<NPRE> gv;
    proj(-1, gv, IntC<1>(), []() {}, []() {}, []() {}, []() {});
#pragma unroll 1
    for (int s = UNI(zero);; s = UNI(s + 1)) {
      gemv_mem<1, A_MEM, false>(gv, w, s, t16_, wofs, near, G, [](uint32_t t) { return t + A_TAB + 8204; }, bars + B_M, zero, trc, [](auto, bool) {});
      sts16f(t16_ + (A_PS - 2048), gv.a[0] + gv.a2[0], gv.a[1] + gv.a2[1], gv.a[2] + gv.a2[2], gv.a[3] + gv.a2[3]);
      sts16f(t16_ + A_PS, gv.b[0] + gv.b2[0], gv.b[1] + gv.b2[1], gv.b[2] + gv.b2[2], gv.b[3] + gv.b2[3]);
      bar_arrive(10 + w4, 64);
      TR(1);
      if (w4 == 0) {
        const uint4 ta = lds16v(t16_ + A_TAB);
        const uint32_t l16 = t16_ - 2048;
        const uint32_t kba = lds4v(t16_ + A_TAB + 8192);
        landed(ta.x & kba & zero);
        bar_sync(7, 160);
        uint32_t kb[8];
        ldm(kb, kba); ldm(kb + 4, kba + 2560);
        scores(kb, l16, ta, []() {});
      } else if (s < NSEG - 1) {
        if (w4 == 1) wait_ft(bars + B_H1 + ((s + 1) & 1) * 8, ((s + 1) >> 1) & 1);
      }
      TR(3);
      bar_sync(9, 256);
      if (s == NSEG - 1) break;
      if (w4 == 2) {
        expect(bars + B_H0, 32768);
        arrive_all<CS>(t16_, A_BARS + B_XE);
      }
      proj(s, gv, IntC<1>(), [&]() __attribute__((always_inline)) {
        if (w4 == 2) {
          wait_ft(bars + B_PAIR, s & 1);
          expect(bars + B_PAIR, 1280);
          wait_ft(bars + B_XE, s & 1);
          fetch_x(A_X, B_H0, s + 1, 0);
        }
        if (w4 == 3) expect(bars + B_M, 16384);
        if (ATT && w4 == 2) asm volatile("fence.proxy.async.shared::cta;" ::: "memory");
        if (w4 == 3) sts4f(bars + B_TK, __uint_as_float(time_offset()));
        BASES();
        char* fp = G + ((wpage(L_FLAG) ^ ((t16 & 16) << 8)) + cta * 4);
        TR(6);
        bar_sync(3, 256);
        const uint32_t tk = lds4v(bars + B_TK + (t16 & zero));
        st_relaxed4_if(fp, ((clk32() * 5 + tk) & ~31u) | (s & 31), ((t16 - SB0) & 0x7E0) == 0x600);
        TR(7);
      }, [&]() __attribute__((always_inline)) {
        if (CHPOS == 0) chores(s);
      }, []() {}, [&]() __attribute__((always_inline)) {
        if (CHPOS == 1) chores(s);
        if (ATT && w4 == 2) sent_qk();
        if (w4 == 3) {
          const char* fl = flag_ptr(G, near, t16_);
          const uint2 f = ld_tagged8(fl);
          const uint32_t tk = lds4(bars + B_TK), su = last_u(f, fl, s, tk);
          const uint32_t tm = next_mem(lds4(bars + B_T + (s & 1) * 4), su, s, d);
          sts4f(bars + B_T + (~s & 1) * 4, __uint_as_float(tm));
          spin_until(tm - 1500, tk);
          spin_until(tm, TKN ? time_offset() : tk);
          TR(12);
          fetch_mem(0);
        }
      });
      TRD(cta);
    }
  }
  if (warp == 6) {
    asm volatile("fence.proxy.async.shared::cta;" ::: "memory");
    send_qk(NSEG - 1);
    sent_qk();
    if (lane < 2) st_relaxed4(G + (wpage(L_FLAG) ^ (lane << 12)) + cta * 4, (NSEG - 1) & 31);
  }
  mbar_wait(bars + B_PAIR, (NSEG - 1) & 1);
  __syncwarp();
  cluster_sync();
  if (tid == 0) STAMP(2);
  if (blockIdx.x == 0) asm volatile("griddepcontrol.wait;" ::: "memory");
}
template <int CS>
__global__ void __launch_bounds__(256, 1)
qk_kernel(const __grid_constant__ CUtensorMap tmWq, const __grid_constant__ CUtensorMap tmWk, const __grid_constant__ CUtensorMap tmX,
          char* __restrict__ G, const Pace d, int zero, int cta0) {
  qk_body<CS>(tmWq, tmWk, tmX, G, d, zero, blockIdx.x + cta0);
}

constexpr int V_WV = 0;
constexpr int V_WO = 32768;
constexpr int V_X = 65536;
constexpr int V_MEM = V_X + 65536;
constexpr int V_U = V_MEM + 16384;
constexpr int V_EX = V_U + 32768;
constexpr int V_VT = V_EX + EX_BYTES;
constexpr int V_OUT = V_VT + 4 * 6144;
constexpr int V_TAB = V_OUT + 4096;
constexpr int V_BARS = V_TAB + 2048;
constexpr int V_RB = V_BARS + 512;
constexpr int V_TB3 = V_RB + 512;
constexpr int V_TRC = V_TB3 + 512;
constexpr int V_SMEM = V_TRC + 512;
constexpr int C_XF = 80  , C_XE = 96  , C_M = 112, C_EXR = 120, C_U = 128  , C_EX = 144, C_EXE = 152, C_T = 160  , C_TK = 164, C_NEAR = 168;
#define VPIN 0
#define VLB 3
#define PF1 1
#define PF0 0
#define OLA 4
#define UPOS 1
#define OPOS 1
#define VDEP 1
#define VC0 3
#define VC1 7
#define VC2 11
#define EXPOS 1
#define VPRE 4
#define VLA 3
#define UW 3
#define RDLY 0
#define VB 0
#define XV 32
#define X0POS 2

#define ACC8(d, o) "+f"(d[o]), "+f"(d[o + 1]), "+f"(d[o + 2]), "+f"(d[o + 3]), "+f"(d[o + 4]), "+f"(d[o + 5]), "+f"(d[o + 6]), "+f"(d[o + 7])
#define OUT8(d, o) "=f"(d[o]), "=f"(d[o + 1]), "=f"(d[o + 2]), "=f"(d[o + 3]), "=f"(d[o + 4]), "=f"(d[o + 5]), "=f"(d[o + 6]), "=f"(d[o + 7])
#define R20 "{%0,%1,%2,%3,%4,%5,%6,%7,%8,%9,%10,%11,%12,%13,%14,%15,%16,%17,%18,%19}"
#define R32 "{%0,%1,%2,%3,%4,%5,%6,%7,%8,%9,%10,%11,%12,%13,%14,%15,%16,%17,%18,%19,%20,%21,%22,%23,%24,%25,%26,%27,%28,%29,%30,%31}"
template <int ACC> __device__ __forceinline__ void wg_ss40(float* d, uint64_t da, uint64_t db) {
  if (ACC) asm volatile("wgmma.mma_async.sync.aligned.m64n40k16.f32.bf16.bf16 " R20 ", %20, %21, 1, 1, 1, 0, 0;"
                        : ACC8(d, 0), ACC8(d, 8), "+f"(d[16]), "+f"(d[17]), "+f"(d[18]), "+f"(d[19]) : "l"(da), "l"(db));
  else asm volatile("wgmma.mma_async.sync.aligned.m64n40k16.f32.bf16.bf16 " R20 ", %20, %21, 0, 1, 1, 0, 0;"
                    : OUT8(d, 0), OUT8(d, 8), "=f"(d[16]), "=f"(d[17]), "=f"(d[18]), "=f"(d[19]) : "l"(da), "l"(db));
}
template <int ACC> __device__ __forceinline__ void wg_rs64(float* d, uint32_t a0, uint32_t a1, uint32_t a2, uint32_t a3, uint64_t db) {
  if (ACC) asm volatile("wgmma.mma_async.sync.aligned.m64n64k16.f32.bf16.bf16 " R32 ", {%32,%33,%34,%35}, %36, 1, 1, 1, 0;"
                        : ACC8(d, 0), ACC8(d, 8), ACC8(d, 16), ACC8(d, 24) : "r"(a0), "r"(a1), "r"(a2), "r"(a3), "l"(db));
  else asm volatile("wgmma.mma_async.sync.aligned.m64n64k16.f32.bf16.bf16 " R32 ", {%32,%33,%34,%35}, %36, 0, 1, 1, 0;"
                    : OUT8(d, 0), OUT8(d, 8), OUT8(d, 16), OUT8(d, 24) : "r"(a0), "r"(a1), "r"(a2), "r"(a3), "l"(db));
}

struct GemvV {
  float a[4], b[4], a2[4], b2[4];
  uint4 m[16];
  uint32_t pp[4][8], z0, c, tg;
  static __device__ __forceinline__ constexpr int blk(int n) { return (n + 12) & 15; }
  static __device__ __forceinline__ constexpr int lm(int n) {
    const int a = n + 1 + VLA + (n < 2 ? 0 : n - 1 > VLB ? VLB : n - 1);
    return a > 16 ? 16 : a;
  }
  __device__ __forceinline__ uint32_t prefetch(uint32_t ws) {
    uint32_t y = ~0u;
#pragma unroll
    for (int j = 0; j < 8; j++) { ldw(pp[j >> 1] + (j & 1) * 4, ws + j * 2048); y &= pp[j >> 1][(j & 1) * 4]; }
    return y;
  }
  __device__ __forceinline__ void first(uint32_t mb) {
#pragma unroll
    for (int n = 0; n < lm(-1); n++) m[n] = lds16v(mb + blk(n) * 512);
  }
  template <int N, int END, typename F> __device__ __forceinline__ void run(const uint32_t* w, uint32_t mb, F hook) {
    if constexpr (N < END) {
      const uint32_t* p = N < 4 ? pp[N & 3] : w + 96 + blk(N) * 8;
      float* d0 = (N & 1) ? a2 : a;
      float* d1 = (N & 1) ? b2 : b;
      if (N < 2) MMA_XZ(d0, p, m[N].x, m[N].y); else MMA_X(d0, p, m[N].x, m[N].y);
      hook(IntC<2 * N>());
      if (N < 2) MMA_XZ(d1, p + 4, m[N].z, m[N].w); else MMA_X(d1, p + 4, m[N].z, m[N].w);
      c |= m[N].x ^ tg;
#pragma unroll
      for (int n = lm(N - 1); n < lm(N); n++) m[n] = lds16v((VDEP ? mb | (c & z0) : mb) + blk(n) * 512);
      hook(IntC<2 * N + 1>());
      run<N + 1, END>(w, mb, hook);
    }
  }
  static constexpr int CV = 31;
};

#undef TKA
#define TKA (bars + C_TK)
template <int CS>
__device__ __forceinline__ void vo_body(const CUtensorMap& tmWv, const CUtensorMap& tmWo, const CUtensorMap& tmX, const CUtensorMap& tmU, const bf16* __restrict__ mem0,
                                        const bf16* __restrict__ xin, char* __restrict__ G, const Pace d, int zero, int block) {
  extern __shared__ __align__(1024) uint8_t smem_raw[];
  const uint32_t sb = smem_u32(smem_raw);
  if ((sb & 0x3FFFF) != SB0) __trap();
  if (block == 0) {
    if (threadIdx.x < 40) { reinterpret_cast<int4*>(g_rings.ctr)[threadIdx.x] = make_int4(-1, -1, -1, -1); __threadfence(); }
    __syncthreads();
  }
  asm volatile("griddepcontrol.launch_dependents;" ::: "memory");
  const int tid = threadIdx.x, t7 = tid & 127, lane = tid & 31;
  const int warp = UNI(tid >> 5), wg = warp >> 2, w4 = warp & 3;
  const uint32_t wofs = UNI((tid >> 5) * -512);
  const int cta = UNI(block), r = cta & 1, head = cta >> 1, fcol = cta * 64, rank = cta & (CS - 1);
  constexpr uint32_t ALL = (1u << CS) - 1;
  const uint32_t bars = sb + V_BARS;
  const uint32_t trc = UNI(sb + V_TRC + (tid >> 5) * 64); (void)trc;
  if (tid == 0) {
    STAMP(0);
    for (int i = 0; i < 20; i++) mbar_init(bars + i * 8, (i * 8 == C_XE || i * 8 == C_XE + 8) ? 4 * CS : i * 8 == C_EXE ? 8 : 1);
    asm volatile("fence.mbarrier_init.release.cluster;" ::: "memory");
  }
  const uint32_t gm = wpage(L_MEM + (head >> 3)) + (head & 7) * 512 + r * 256;
  {
    const uint4 z = make_uint4(0, 0, 0, 0);
    *reinterpret_cast<uint4*>(G + ((wpage(L_VM + head) + r * 2048 + t7 * 16) ^ (wg << 12))) = z;
    for (int i = 0; i < 4; i++) *reinterpret_cast<uint4*>(G + ((wpage(cta) ^ ((i & 1) << 12)) + VX0 + (i >> 1) * 16384 + tid * 16)) = z;
    if (tid < 64) {
      const uint32_t* m0 = reinterpret_cast<const uint32_t*>(mem0) + (4 * r + (lane >> 3)) * (DM / 2) + head * 16 + (lane & 1) * 8 + ((lane & 7) >> 1);
      char* p = G + ((gm + lane * 8) ^ (warp << 12));
      *reinterpret_cast<uint2*>(p) = make_uint2(0, 0);
      *reinterpret_cast<uint2*>(p + 16384) = make_uint2(m0[0], m0[4]);
    }
  }
  __syncthreads();
  const uint32_t stg = sb + V_X + wg * 65536;
  const uint32_t sbar = bars + wg * 32;
  const int lk = (lane & 7) + ((lane >> 4) << 3);
  const uint32_t wt_off = lk * 128 + (((((tid >> 4) & 6) + ((lane >> 3) & 1)) ^ (lk & 7)) << 4);
  const int g = lane >> 2, c = lane & 3;
  if (t7 == 0) {
    for (int i = 0; i < 4; i++) {
      mbar_expect_tx(sbar + i * 8, 16384);
      for (int t = 0; t < 2; t++)
        tma2d(stg + i * 16384 + t * 8192, &tmWo, head * 32, r * 2048 + (wg * 4 + i) * 256 + t * 128, sbar + i * 8);
    }
    if (wg == 0) {
      mbar_expect_tx(bars + B_RES, 32768);
      for (int i = 0; i < 2; i++) tma2d_ef(sb + V_WV + i * 16384, &tmWv, fcol, i * 512 + 384, bars + B_RES);
    }
  }
  if (tid == 32 && cta < XP) asm volatile("cp.async.bulk.prefetch.L2.global [%0], 32768;" ::"l"(xin + (size_t)cta * 16384) : "memory");
  if (tid == 64) start_barrier();
  if (tid == 96) sts4f(bars + C_NEAR, __uint_as_float(probe_near(G, 64 + cta)));
  __syncwarp();
  uint32_t w[192];
  const uint32_t t16_ = OPQ(sb + tid * 16);
  mbar_wait(sbar + w4 * 8, 0);
  {
    const int rr = lane & 7, mi = lane >> 3, cc = rr >> 1;
    const uint32_t a = stg + w4 * 16384 + ((cc >> 1) * 16 + (cc & 1) * 4 + (mi >> 1) * 8 + (rr & 1)) * 64 + (mi & 1) * 32;
    const int sl0 = (g >> 1) * 8 + c;
#pragma unroll
    for (int j = 0; j < 16; j++)
#pragma unroll
      for (int t = 0; t < 2; t++) {
        uint32_t x0, x1, x2, x3;
        ldsm4t(x0, x1, x2, x3, a + ((j >> 1) * 32 + (j & 1) * 2) * 64 + t * 16);
        const uint32_t e0 = __shfl_sync(~0u, x0, sl0), e1 = __shfl_sync(~0u, x1, sl0);
        const uint32_t q0 = __shfl_sync(~0u, x0, sl0 + 4), q1 = __shfl_sync(~0u, x1, sl0 + 4);
        const uint32_t e2 = __shfl_sync(~0u, x2, sl0), e3 = __shfl_sync(~0u, x3, sl0);
        const uint32_t q2 = __shfl_sync(~0u, x2, sl0 + 4), q3 = __shfl_sync(~0u, x3, sl0 + 4);
        const uint4 f = (g & 1) ? make_uint4(e1, q1, e3, q3) : make_uint4(e0, q0, e2, q2);
        const int o = (j * 2 + t) * 4 - 32;
        if (o < 0) sts16(t16_ + V_WO + (j * 2 + t) * 4096, f);
        else { w[o] = f.x; w[o + 1] = f.y; w[o + 2] = f.z; w[o + 3] = f.w; }
      }
  }
  bar_sync(1 + wg, 128);
  if (t7 == 0)
    for (int i = 0; i < 3; i++) {
      mbar_expect_tx(sbar + i * 8, 16384);
      tma2d_ef(stg + i * 16384, &tmWv, fcol, wg * 512 + i * 128, sbar + i * 8);
    }
#pragma unroll
  for (int j = 0; j < 24; j++) {
    if ((j & 7) == 0) mbar_wait(sbar + (j >> 3) * 8, 1);
    ldw(w + 96 + j * 4, stg + j * 2048 + wt_off);
  }
  mbar_wait(bars + B_RES, 0);
  if (tid == 32) {
    asm volatile("cp.async.bulk.prefetch.L2.global [%0], 32768;" ::"l"(xin + (size_t)(64 + cta) * 16384) : "memory");
    if (cta >= XP) asm volatile("cp.async.bulk.prefetch.L2.global [%0], 32768;" ::"l"(xin + (size_t)cta * 16384) : "memory");
  }
  cluster_sync();
  if (tid == 0) STAMP(1);
  const uint32_t near = UNI(lds4(bars + C_NEAR));
  const uint32_t rdelta = UNI(mapa(sb, rank ^ 1) - sb);
  const uint32_t qside = ld_relaxed4(&g_rings.side[cta]);
  const uint32_t vxo = UNI(plo(G) + (wpage(cta) ^ qside) + VX0 + (tid >> 5) * 512 - sb);
  sts8f(sb + V_TAB + tid * 8, __uint_as_float(sb + V_WV + (tid >> 7) * 16384 + wt_off),
        __uint_as_float(sb + V_VT + (((tid >> 4) & 4) + ((lane & 7) >> 1)) * 768 + (((tid >> 3) & 4) + (lane & 1)) * 16));
  if (tid < 32) {
    const char* mp = G + ((gm ^ near ^ 4096) + lane * 8);
    sts16(t16_ + V_TB3, make_uint4(plo(mp), phi(mp), plo(mp) ^ 4096, phi(mp)));
  }
  const uint32_t tabo = UNI((sb >> 1) + V_TAB), vmo = UNI(plo(G) + ((wpage(L_VM + head) ^ qside) + r * 2048) - (sb >> 1));
  auto TAB = [&](uint32_t t) __attribute__((always_inline)) {
    uint32_t a; asm volatile("{.reg .u32 x; shr.u32 x, %1, 1; add.u32 %0, x, %2;}" : "=r"(a) : "r"(t), "r"(tabo)); return a;
  };
  if (warp == 0) sts8f(bars + C_T, 0.f, __uint_as_float(time_offset()));
  auto fetch_x = [&](int n, int h) __attribute__((always_inline)) {
    if (n > 0) wait_ft(bars + C_XE + h * 8, (n - 1) & 1);
    expect(bars + C_XF + h * 8, 32768);
    issue_x(&tmX, sb + V_X + h * 32768 + rank * (32768 / CS), bars + C_XF + h * 8, n, h * 8 + rank * (8 / CS), ALL);
  };
  auto release_x = [&](int h) __attribute__((always_inline)) { arrive_all<CS>(t16_, V_BARS + C_XE + h * 8); };
  auto fetch_mem = [&](uint32_t slot) __attribute__((always_inline)) { fetch_mem_mc<CS>(sb + V_MEM, G, near + slot, rank, bars + C_M); };
  auto fetch_ex = [&](int n) __attribute__((always_inline)) {
    {
      if (n > 0) wait_ft(bars + C_EXE, (n - 1) & 1);
      expect(bars + C_EX, EX_BYTES);
      const char* src = reinterpret_cast<const char*>(g_rings.ex[n & 3]) + head * EX_BYTES;
      const uint32_t dst = sb + V_EX;
      if (r != head >> 4) { }
      else if (rank < 2) bulk_mc<3>(dst, src, EX_BYTES, bars + C_EX);
      else if (rank < 4) bulk_mc<12>(dst, src, EX_BYTES, bars + C_EX);
      else if (rank < 6) bulk_mc<48>(dst, src, EX_BYTES, bars + C_EX);
      else bulk_mc<192>(dst, src, EX_BYTES, bars + C_EX);
    }
    __syncwarp();
  };
  auto release_ex = [&]() __attribute__((always_inline)) {
    BASES();
    if ((t16 & 0x1E0) == 0) mbar_arrive_cluster(mapa(SB0 + V_BARS + C_EXE, ((t16 >> 4) & 1) ^ rank));
    __syncwarp();
  };
  auto vproj1 = [&](int n, bool gate, GemvV& gv, uint32_t ws, auto mid) __attribute__((always_inline)) {
    float d[16];
    if (PF1 == 0) gv.prefetch(ws);
    wait_ft(bars + C_XF + 8, n & 1);
    if (gate) bar_sync(6, 160);
    if (PF1 == 1) gv.prefetch(ws);
    WG_FENCE();
#pragma unroll
    for (int k = 0; k < XV; k++) {
      const uint64_t b = cdesc(0, V_X + 32768 + xk(k));
      if (k == 0) wg_rs32<0>(d, w + 96, b);
      else if (k < 24) wg_rs32<1>(d, w + 96 + k * 4, b);
      else wg_rs32<1>(d, gv.pp[(k - 24) >> 1] + (k & 1) * 4, b);
      if (VB && gate && k == VB - 1) bar_sync(5, 160);
    }
    WG_COMMIT();
    mid();
    WG_WAIT(0);
    acc_fence16(d);
#pragma unroll
    for (int i = 0; i < 4; i++) sts16f(t16_ + (V_X + 32768 - 2048) + i * 2048, d[4 * i], d[4 * i + 1], d[4 * i + 2], d[4 * i + 3]);
  };
  auto vproj0 = [&](int n, auto mid, auto next) __attribute__((always_inline)) {
    float d[16];
#pragma unroll
    for (int i = 0; i < 4; i++) {
      const float4 p = lds16f(t16_ + V_X + 32768 + i * 2048);
      d[4 * i] = p.x; d[4 * i + 1] = p.y; d[4 * i + 2] = p.z; d[4 * i + 3] = p.w;
    }
    wait_ft(bars + C_XF, n & 1);
    acc_fence16(d);
    release_x(1);
    WG_FENCE();
#pragma unroll
    for (int k = 0; k < XV; k++) {
      const uint64_t b = cdesc(0, V_X + xk(k));
      if (k < 24) wg_rs32<1>(d, w + 96 + k * 4, b);
      else wg_ss32(d, cdesc(0, V_WV + (k - 24) * 2048), b);
    }
    WG_COMMIT();
    mid();
    BASES();
    const uint32_t vt = lds4(TAB(t16) + 4) + (n & 3) * 6144 + (t16 & 384);
    const uint32_t tx = (~n & 2) << 15;
    WG_WAIT(0);
    acc_fence16(d);
    const uint4 f0 = make_uint4(pack_tag(d[0], d[1], tx), pack_bf16(d[4], d[5]), pack_bf16(d[8], d[9]), pack_bf16(d[12], d[13]));
    const uint4 f1 = make_uint4(pack_tag(d[2], d[3], tx), pack_bf16(d[6], d[7]), pack_bf16(d[10], d[11]), pack_bf16(d[14], d[15]));
    release_x(0);
    if (ATT) { stsm4(vt, pack_bf16(d[0], d[1]), f0.y, f0.z, f0.w); stsm4(vt + 32, pack_bf16(d[2], d[3]), f1.y, f1.z, f1.w); }
    next();
    char* dst = ptr64(t16 + (vxo + (n & 1) * 16384) + (clk32() & zero), phi(G));
    if (!(EXPT & 2) || zero) { st_tagged16(dst, f0); st_tagged16(dst + 512, f1); }
  };
  auto attention = [&](int n) __attribute__((always_inline)) {
    float sa[20];
    wait_ft(bars + C_EX, n & 1);
    WG_FENCE();
#pragma unroll
    for (int k = 0; k < 8; k++) {
      const int o = V_EX + (k >> 2) * EX_CTA;
      const uint64_t da = ndesc(0, o + (k & 3) * 1024, 128, 128), db = ndesc(0, o + EX_K + (k & 3) * 1280, 640, 128);
      if (k == 0) wg_ss40<0>(sa, da, db); else wg_ss40<1>(sa, da, db);
    }
    WG_COMMIT();
    BASES();
    const int row = (int)(((t16 - SB0) >> 6) & 31);
    const int dlt = row - (int)((t16 >> 3) & 6);
    WG_WAIT(0);
    asm volatile("" : ACC8(sa, 0), ACC8(sa, 8), "+f"(sa[16]), "+f"(sa[17]), "+f"(sa[18]), "+f"(sa[19])::"memory");
    release_ex();
    float sc[10];
#pragma unroll
    for (int i = 0; i < 8; i++) sc[i] = dlt >= (i >> 1) * 8 + (i & 1) ? sa[(i >> 1) * 4 + (i & 1)] * SCL : -INFINITY;
    sc[8] = sa[16] * SCL; sc[9] = sa[17] * SCL;
    exp10v(sc);
    uint32_t p[5];
#pragma unroll
    for (int i = 0; i < 5; i++) p[i] = pack_bf16(sc[2 * i], sc[2 * i + 1]);
    float o[32];
    const uint32_t z = (n & 3) * 384;
    const uint32_t j0 = junk(), j1 = junk(), j2 = junk(), j3 = junk(), j4 = junk(), j5 = junk();
    float sum = (((sc[0] + sc[1]) + (sc[2] + sc[3])) + ((sc[4] + sc[5]) + (sc[6] + sc[7]))) + (sc[8] + sc[9]);
    const uint32_t p5 = p[4] | (__float_as_uint(sum) & zero);
    WG_FENCE();
    wg_rs64<0>(o, p[0], j0, p[1], j1, ndesc(z, V_VT, 128, 768));
    wg_rs64<1>(o, p[2], j2, p[3], j3, ndesc(z, V_VT + 256, 128, 768));
    wg_rs64<1>(o, p[4], j4, p5, j5, ndesc(z, V_VT + 512, 128, 768));
    WG_COMMIT();
    sum += __uint_as_float(clk32() & zero);
    sum += __shfl_xor_sync(~0u, sum, 1);
    sum += __shfl_xor_sync(~0u, sum, 2);
    const float inv = rcp_fast(sum);
    WG_WAIT(0);
    asm volatile("" : ACC8(o, 0), ACC8(o, 8), ACC8(o, 16), ACC8(o, 24)::"memory");
    asm volatile("cp.async.bulk.wait_group.read 0;" ::: "memory");
    __syncwarp();
    const uint32_t oa = sb + V_OUT + row * 128 + (((t16 & 48) ^ (row << 4)) & 0x70);
    sts16(oa, make_uint4(pack_bf16(o[0] * inv, o[1] * inv), pack_bf16(o[4] * inv, o[5] * inv), pack_bf16(o[8] * inv, o[9] * inv), pack_bf16(o[12] * inv, o[13] * inv)));
    sts16(oa ^ 64, make_uint4(pack_bf16(o[16] * inv, o[17] * inv), pack_bf16(o[20] * inv, o[21] * inv), pack_bf16(o[24] * inv, o[25] * inv), pack_bf16(o[28] * inv, o[29] * inv)));
  };
  auto store_o = [&](int n) __attribute__((always_inline)) {
    asm volatile(ELECT "cp.async.bulk.tensor.2d.global.shared::cta.bulk_group [%0, {%2, %3}], [%1];}"
                 ::"l"(&tmU), "r"(sb + (V_OUT - 4096) - wofs * 2), "r"(fcol), "r"((n & 127) * SEG + w4 * 8) : "memory");
    asm volatile("cp.async.bulk.commit_group;" ::: "memory");
  };
  if (warp == 2) { fetch_x(0, 1); fetch_x(0, 0); expect(bars + C_M, 16384); fetch_mem(16384); }
  if (tid == 32) mbar_expect_tx(bars + B_PAIR, 512);
  __syncthreads();
  GemvV gv;
  if (wg) vproj1(0, false, gv, lds4(TAB(t16_)), []() {});
  __syncthreads();
  auto gemv_v = [&](int s, auto wg_c, auto end) __attribute__((always_inline)) {
    constexpr int wg = decltype(wg_c)::value;
    const uint32_t tg = (s & 1) << 16;
    uint32_t tv;
    gemv_mem<wg, V_MEM, wg == 0>(gv, w, s, t16_, wofs, near, G, [&](uint32_t t) __attribute__((always_inline)) { return TAB(t); }, bars + C_M, zero, trc,
                         [&](auto nc, bool) __attribute__((always_inline)) { if (decltype(nc)::value == 26) tv = lds4v(TAB(t16_ | (gv.m[14].x & zero)) + 4); });
#pragma unroll
    for (int i = 0; i < 4; i++) gv.a[i] = (gv.a[i] + gv.b[i]) + (gv.a2[i] + gv.b2[i]);
    const uint32_t m0 = pack_tag(gv.a[0], gv.a[1], tg ^ TAG), m1 = pack_bf16(gv.a[2], gv.a[3]);
    BASES();
    st_tagged8(ptr64(((t16 >> 1) + vmo), phi(G)), m0, m1);
    if (ATT) {
      const uint32_t vt = tv + (s & 3) * 6144 + (512 + wg * 128) + ((t16 >> 2) & 32);
      asm volatile("stmatrix.sync.aligned.m8n8.x2.shared.b16 [%0], {%1, %2};" ::"r"(vt), "r"(pack_bf16(gv.a[0], gv.a[1])), "r"(m1) : "memory");
    }
    end();
    TR(1);
    bar_sync(4, 256);
  };
  uint32_t w0[32], wsv;
  auto pre_o = [&]() __attribute__((always_inline)) {
#pragma unroll
    for (int i = 0; i < 8; i++) { const uint4 t = lds16v(t16_ + V_WO + i * 4096); w0[4 * i] = t.x; w0[4 * i + 1] = t.y; w0[4 * i + 2] = t.z; w0[4 * i + 3] = t.w; }
  };
  auto gemv_o = [&](int s, auto wg_c, auto look) __attribute__((always_inline)) {
    constexpr int wg = decltype(wg_c)::value;
    const uint32_t tu = (~s & 1) << 16;
    float a0[4], a1[4], a2[4], a3[4];
    uint4 uv[8];
    auto mul = [&](auto hook) __attribute__((always_inline)) {
#pragma unroll
      for (int i = 0; i < 8; i++) {
        const uint32_t* p = i < 2 ? w0 + 16 : w + (i * 16 - 32);
        if (i == 0) { MMA_XZ(a0, w0, uv[0].x, uv[0].y); MMA_XZ(a1, w0 + 4, uv[0].x, uv[0].y); MMA_XZ(a2, w0 + 8, uv[0].z, uv[0].w); MMA_XZ(a3, w0 + 12, uv[0].z, uv[0].w); }
        else { MMA_X(a0, p, uv[i].x, uv[i].y); MMA_X(a1, p + 4, uv[i].x, uv[i].y); MMA_X(a2, p + 8, uv[i].z, uv[i].w); MMA_X(a3, p + 12, uv[i].z, uv[i].w); }
        hook(i);
      }
    };
    BASES();
    const uint32_t ub = t16 + (V_U + wofs * -7);
    landed(zero & w0[0] & w0[4] & w0[8] & w0[12] & w0[16] & w0[20] & w0[24] & w0[28]);
    wait_ft(bars + C_U + wg * 8, s & 1);
    TR(4);
#pragma unroll
    for (int i = 0; i < OLA; i++) uv[i] = lds16v(ub + i * 512);
    uint32_t cc = 0;
    mul([&](int i) __attribute__((always_inline)) {
      cc |= uv[i].x ^ tu;
      if (i + OLA < 8) uv[i + OLA] = lds16v(ub + (i + OLA) * 512);
      if (wg == 1 && i + OLA == 7) wsv = lds4v(TAB(t16));
      if (i == 1) look();
    });
    const bool bad = __any_sync(~0u, (int)(cc << 15) < 0);
    if (__builtin_expect(bad, 0)) {
      CNT(3);
      const char* src = G + ((wpage(L_U + r * 8 + warp) ^ near) + (t16 & 0x1F0));
      for (int it = 0;; it++) {
        uint32_t c2 = 0;
#pragma unroll
        for (int i = 0; i < 8; i++) uv[i] = ld_tagged16(src + i * 512);
#pragma unroll
        for (int i = 0; i < 8; i++) chk2(c2, uv[i], tu);
        if (!__any_sync(~0u, c2 & TAG)) break;
        if (it > POLL_LIMIT) FAIL(4000);
      }
#pragma unroll
      for (int i = 4; i < 8; i++) sts16(ub + i * 512, uv[i]);
      pre_o();
      mul([&](int i) __attribute__((always_inline)) { if (i < 4) uv[i + 4] = lds16v(ub + (i + 4) * 512); });
    }
    const uint32_t owr = (t16 & 48) * 16 + (((t16 >> 2) ^ (t16 * 2)) & 0x70) + (sb + V_U + wofs * -8);
    sts16f(owr, a0[0] + a2[0], a0[2] + a2[2], a1[0] + a3[0], a1[2] + a3[2]);
    sts16f(owr + 128, a0[1] + a2[1], a0[3] + a2[3], a1[1] + a3[1], a1[3] + a3[3]);
  };
  auto sum8 = [&](uint32_t ra, float* sm) __attribute__((always_inline)) {
    float4 p[8];
#pragma unroll
    for (int i = 0; i < 8; i++) p[i] = lds16f(ra + i * 4096);
    sm[0] = ((p[0].x + p[1].x) + (p[2].x + p[3].x)) + ((p[4].x + p[5].x) + (p[6].x + p[7].x));
    sm[1] = ((p[0].y + p[1].y) + (p[2].y + p[3].y)) + ((p[4].y + p[5].y) + (p[6].y + p[7].y));
    sm[2] = ((p[0].z + p[1].z) + (p[2].z + p[3].z)) + ((p[4].z + p[5].z) + (p[6].z + p[7].z));
    sm[3] = ((p[0].w + p[1].w) + (p[2].w + p[3].w)) + ((p[4].w + p[5].w) + (p[6].w + p[7].w));
  };
  if (wg == 0) {
    vproj0(0, [&]() __attribute__((always_inline)) { if (w4 == 2) fetch_x(1, 1); }, []() {});
    if (w4 == 2) fetch_x(1, 0);
#pragma unroll 1
    for (int s = UNI(zero);; s = UNI(s + 1)) {
      gemv_v(s, IntC<0>(), []() {});
      if (s == NSEG - 1) break;
      uint32_t tu = 0;
      auto do_u = [&]() __attribute__((always_inline)) {
          auto fetch_u = [&](auto r_c) __attribute__((always_inline)) {
            constexpr int r = decltype(r_c)::value;
#pragma unroll
            for (int t = 1; t >= 0; t--) {
              spin_until(t ? tu : tu + d.s, 0);
              if (t) TR(12);
#pragma unroll
              for (int i = 0; i < 8 / CS; i++) {
                const int j = (rank >> 1) * (8 / CS) + i;
                const char* src = G + ((wpage(L_U + r * 8 + t * 4) ^ near) + ((j & 1) << 18) + ((j & 2) << 19));
                if (CS > 2) bulk_mc<(0x55u << r) & ALL>(sb + V_U + t * 16384 + j * 4096, src, 4096, bars + C_U + t * 8);
                else bulk(sb + V_U + t * 16384 + j * 4096, src, 4096, bars + C_U + t * 8);
              }
            }
          };
          if (r) fetch_u(IntC<1>()); else fetch_u(IntC<0>());
      };
      vproj0(s + 1, [&]() __attribute__((always_inline)) {
        if (w4 == 2 && s + 2 < NSEG) fetch_x(s + 2, 1);
        if (w4 == 3) {
          expect(bars + C_M, 16384); expect(bars + C_U, 16384); expect(bars + C_U + 8, 16384);
          const uint32_t tk = TKN ? time_offset() : lds4(bars + C_TK);
          tu = time_u(lds4(bars + C_T), s, d);
          if (s == 0) { const char* fl = flag_ptr(G, near, t16_); tu = last_u(ld_tagged8(fl), fl, 0, tk); }
          LOGT(tu - d.u);
          tu -= tk;
          if (UPOS == 0) do_u();
        }
      }, pre_o);
      TR(2);
      if (UPOS == 1 && w4 == 3) do_u();
      uint2 f = make_uint2(0, 0);
      gemv_o(s, IntC<0>(), [&]() __attribute__((always_inline)) {
        asm volatile("{.reg .pred q; setp.ne.u32 q, %3, 0; @q ld.relaxed.gpu.global.v2.u32 {%0,%1}, [%2];}"
                     : "+r"(f.x), "+r"(f.y) : "l"(flag_ptr(G, near, t16_)), "r"((uint32_t)(w4 == 0)) : "memory");
      });
      TR(5);
      BASES();
      const uint32_t tp = (r ^ 1) * 4 + w4;
      const uint32_t ra = (((t16 >> 2) & 0x7C) ^ ((tp & 6) << 4)) + (sb + V_U + tp * 128);
      bar_sync(3, 256);
      {
        float p[8];
#pragma unroll
        for (int i = 0; i < 8; i++) p[i] = lds4f(ra + i * 4096);
        st_async4((t16 >> 2) + (sb - (sb >> 2) + V_RB + rdelta), (((p[0] + p[1]) + (p[2] + p[3])) + (p[4] + p[5])) + (p[6] + p[7]), bars + B_PAIR + rdelta);
      }
      TR(6);
      if (w4 == 1) {
        float sm[4];
        sum8(((t16 & 0x1F0) ^ ((t16 >> 3) & 0x20) ^ (r << 6)) + (sb + V_U + r * 512), sm);
        const uint4 t3 = lds16v(t16_ + (V_TB3 - 512));
        landed(__float_as_uint(sm[0]) & t3.x & zero);
        bar_arrive(6, 160);
        wait_ft(bars + B_PAIR, s & 1);
        TR(7);
        const float4 q = lds16f(t16_ + (V_RB - 512));
        const uint32_t m0 = pack_tag(sm[0] + q.x, sm[1] + q.y, (~s & 1) << 16), m1 = pack_bf16(sm[2] + q.z, sm[3] + q.w);
        st_tagged8(ptr64(t3.x, t3.y), m0, m1);
        st_tagged8(ptr64(t3.z, t3.w), m0, m1);
        TR(8);
        if (VB) bar_arrive(5, 160);
        expect(bars + B_PAIR, 512);
      } else if (w4 == 0) {
        const uint32_t tk = time_offset();
        const uint32_t tm = next_mem(lds4(bars + C_T), last_u(f, flag_ptr(G, near, t16_), s, tk), s, d);
        sts8f(bars + C_T, __uint_as_float(tm), __uint_as_float(tk));
        spin_until(tm, tk);
        TR(9);
        fetch_mem(0);
      } else if (w4 == 2) {
        if (ATT && s >= 1) fetch_ex(s - 1);
      } else if (X0POS == 1 && s + 2 < NSEG) fetch_x(s + 2, 0);
      TRD(64 + cta);
    }
  } else {
    vproj1(1, false, gv, lds4(TAB(t16_)), []() {});
#pragma unroll 1
    for (int s = UNI(zero);; s = UNI(s + 1)) {
      gemv_v(s, IntC<1>(), []() {});
      if (ATT && OPOS == 0) store_o(s - 3);
      if (s == NSEG - 1) break;
      if (ATT && s >= 2) attention(s - 2);
      pre_o();
      TR(2);
      gemv_o(s, IntC<1>(), []() {});
      TR(5);
      bar_arrive(3, 256);
      if (ATT) asm volatile("fence.proxy.async.shared::cta;" ::: "memory");
      if (X0POS == 2 && w4 == 2 && s + 2 < NSEG) fetch_x(s + 2, 0);
      if (s + 2 < NSEG) vproj1(s + 2, true, gv, wsv, []() {}); else {
        bar_sync(6, 160);
        if (VB) bar_sync(5, 160);
        gv.prefetch(wsv);
      }
      if (ATT && OPOS == 1) store_o(s - 2);
      TR(7);
      TRD(64 + cta);
    }
  }
  if (ATT) {
    asm volatile("fence.proxy.async.shared::cta;" ::: "memory");
    __syncthreads();
#pragma unroll 1
    for (int n = NSEG - 3; n < NSEG; n++) {
      if (warp == 1 && n > NSEG - 3) {
        const char* fl = flag_ptr(G, near, t16_);
        last_u(ld_tagged8(fl), fl, NSEG - 1, 0);
        fetch_ex(n);
      }
      if (wg) {
        attention(n);
        asm volatile("fence.proxy.async.shared::cta;" ::: "memory");
        __syncwarp();
        store_o(n);
      }
    }
  }
  if (wg) {
    asm volatile("cp.async.bulk.wait_group 0;" ::: "memory");
    __syncwarp();
    if (lane == 0) { __threadfence(); atomicAdd(&g_rings.ctr[3][0], 1); }
  }
  __syncwarp();
  cluster_sync();
  if (tid == 0) STAMP(2);
}
template <int CS>
__global__ void __launch_bounds__(256, 1)
vo_kernel(const __grid_constant__ CUtensorMap tmWv, const __grid_constant__ CUtensorMap tmWo, const __grid_constant__ CUtensorMap tmX,
          const __grid_constant__ CUtensorMap tmU, const bf16* __restrict__ mem0, const bf16* __restrict__ xin, char* __restrict__ G, const Pace d, int zero) {
  vo_body<CS>(tmWv, tmWo, tmX, tmU, mem0, xin, G, d, zero, blockIdx.x);
}

__device__ uint32_t g_z1[512 * S_LEN];
__device__ uint32_t g_z2[512 * S_LEN];
__device__ __align__(16) uint32_t g_wt[513 * S_LEN];

__device__ __forceinline__ float2 cmul(float2 a, float2 b) { return make_float2(fmaf(a.x, b.x, -a.y * b.y), fmaf(a.x, b.y, a.y * b.x)); }
__device__ __forceinline__ float2 unpack_bf16(uint32_t v) { return make_float2(__uint_as_float(v << 16), __uint_as_float(v & 0xFFFF0000u)); }
__host__ __device__ constexpr float cos32(int i) {
  return i == 0 ? 1.f : i == 1 ? 0.98078528040323044913f : i == 2 ? 0.92387953251128675613f : i == 3 ? 0.83146961230254523708f
       : i == 4 ? 0.70710678118654752440f : i == 5 ? 0.55557023301960222474f : i == 6 ? 0.38268343236508977173f
       : i == 7 ? 0.19509032201612826785f : 0.f;
}
template <int I, int DIR> __device__ __forceinline__ float2 rot32(float2 v) {
  if constexpr (I == 0) return v;
  else if constexpr (I == 8) return DIR > 0 ? make_float2(-v.y, v.x) : make_float2(v.y, -v.x);
  else {
    constexpr float cs = I < 8 ? cos32(I) : -cos32(16 - I);
    constexpr float sn = (I < 8 ? cos32(8 - I) : cos32(I - 8)) * DIR;
    if constexpr (I == 4 || I == 12) {
      constexpr float sgn = (cs > 0) == (sn > 0) ? 1.f : -1.f;
      return make_float2(cs * (v.x - sgn * v.y), cs * (v.y + sgn * v.x));
    } else return make_float2(fmaf(v.x, cs, -v.y * sn), fmaf(v.x, sn, v.y * cs));
  }
}
template <int N, int DIR, int K> struct Comb {
  static __device__ __forceinline__ void run(const float2* e, const float2* o, float2* out) {
    if constexpr (K < N / 2) {
      const float2 t = rot32<K * (32 / N), DIR>(o[K]);
      out[K] = make_float2(e[K].x + t.x, e[K].y + t.y);
      out[K + N / 2] = make_float2(e[K].x - t.x, e[K].y - t.y);
      Comb<N, DIR, K + 1>::run(e, o, out);
    }
  }
};
template <int N, int DIR, int ST> __device__ __forceinline__ void fft_r(const float2* in, float2* out) {
  if constexpr (N == 1) out[0] = in[0];
  else {
    float2 e[N / 2], o[N / 2];
    fft_r<N / 2, DIR, ST * 2>(in, e);
    fft_r<N / 2, DIR, ST * 2>(in + ST, o);
    Comb<N, DIR, 0>::run(e, o, out);
  }
}
template <int N, int DIR> __device__ __forceinline__ void fft_reg(float2* v) {
  float2 t[N];
  fft_r<N, DIR, 1>(v, t);
#pragma unroll
  for (int i = 0; i < N; i++) v[i] = t[i];
}
template <int N> __device__ __forceinline__ void twiddle(float2* v, float x) {
  float2 p[N];
  sincospif(x, &p[1].y, &p[1].x);
#pragma unroll
  for (int k = 2; k < N; k++) p[k] = cmul(p[k / 2], p[k - k / 2]);
#pragma unroll
  for (int k = 1; k < N; k++) v[k] = cmul(v[k], p[k]);
}

constexpr int F1_LD = 16 * 33 - 1;
constexpr int F1_SMEM = 16 * F1_LD * 8;
__device__ __forceinline__ void fft_rows_fwd(float2* fs, int item, const bf16* __restrict__ x, const bf16* __restrict__ wr, const bf16* __restrict__ wi) {
  const int tid = threadIdx.x, s0 = item * 16;
  {
    const int row = tid >> 4, t = tid & 15;
    const uint2* src = reinterpret_cast<const uint2*>(x + (size_t)(s0 + row) * DM) + t;
    float2 a[16], b[16];
#pragma unroll
    for (int i = 0; i < 16; i++) { const uint2 v = __ldg(src + i * 16); a[i] = unpack_bf16(v.x); b[i] = unpack_bf16(v.y); }
    fft_reg<16, -1>(a); twiddle<16>(a, -(float)(2 * t) / 256.f);
    float2* d = fs + row * F1_LD + t;
#pragma unroll
    for (int i = 0; i < 16; i++) d[i * 33] = a[i];
    fft_reg<16, -1>(b); twiddle<16>(b, -(float)(2 * t + 1) / 256.f);
#pragma unroll
    for (int i = 0; i < 16; i++) d[i * 33 + 16] = b[i];
  }
  __syncthreads();
  {
    const int row = tid & 15, k2 = tid >> 4;
    float2 v[32];
#pragma unroll
    for (int i = 0; i < 32; i++) v[i] = fs[row * F1_LD + k2 * 33 + (i >> 1) + (i & 1) * 16];
    fft_reg<32, -1>(v);
#pragma unroll
    for (int i = 0; i < 32; i++) g_z1[(k2 + 16 * i) * S_LEN + s0 + row] = pack_bf16(v[i].x, v[i].y);
  }
  {
    __syncthreads();
    uint4* sw = reinterpret_cast<uint4*>(fs);
    const uint4* pr = reinterpret_cast<const uint4*>(wr + (size_t)s0 * 513);
    const uint4* pi = reinterpret_cast<const uint4*>(wi + (size_t)s0 * 513);
#pragma unroll
    for (int q = 0; q < 5; q++) {
      const int i = tid + q * 256;
      if (i < 1026) { sw[i] = __ldg(pr + i); sw[1026 + i] = __ldg(pi + i); }
    }
    __syncthreads();
    const uint16_t* hr = reinterpret_cast<const uint16_t*>(fs) + (tid & 3) * 4 * 513;
    const uint16_t* hi = hr + 1026 * 8;
#pragma unroll
    for (int q = 0; q < 9; q++) {
      const int k = (tid >> 2) + q * 64;
      if (q == 8 && k != 512) break;
      uint32_t o[4];
#pragma unroll
      for (int r = 0; r < 4; r++) o[r] = (uint32_t)hr[r * 513 + k] | ((uint32_t)hi[r * 513 + k] << 16);
      *reinterpret_cast<uint4*>(g_wt + k * S_LEN + s0 + (tid & 3) * 4) = make_uint4(o[0], o[1], o[2], o[3]);
    }
  }
}

constexpr int F2_LD = 2048 + 128;
__device__ __forceinline__ int f2_pad(int i) { return i + (i >> 7); }
__device__ __forceinline__ void fft_cols(float2* fs, int item) {
  const int tid = threadIdx.x, half = tid >> 7, t = tid & 127;
  const int k = item == 0 ? half * 256 : (half ? 512 - item : item);
  float2* my = fs + half * F2_LD;
  const float2* mir = fs + (item == 0 ? half : half ^ 1) * F2_LD;
  float2 v[16];
#pragma unroll
  for (int a = 0; a < 16; a++) v[a] = unpack_bf16(__ldcg(&g_z1[k * S_LEN + t + 128 * a]));
  fft_reg<16, -1>(v); twiddle<16>(v, -(float)t / 1024.f);
#pragma unroll
  for (int i = 0; i < 16; i++) my[f2_pad(i * 128 + t)] = v[i];
  bar_sync(1 + half, 128);
  const int t0 = t & 15, kp = t >> 4;
#pragma unroll
  for (int h = 0; h < 2; h++) {
#pragma unroll
    for (int b = 0; b < 8; b++) v[h * 8 + b] = my[f2_pad((2 * kp + h) * 128 + t0 + 16 * b)];
    fft_reg<8, -1>(v + h * 8);
  }
  float2 p8[8];
  sincospif(-(float)t0 / 64.f, &p8[1].y, &p8[1].x);
#pragma unroll
  for (int i = 2; i < 8; i++) p8[i] = cmul(p8[i / 2], p8[i - i / 2]);
#pragma unroll
  for (int h = 0; h < 2; h++)
#pragma unroll
    for (int b = 0; b < 8; b++)
      my[f2_pad((2 * kp + h) * 128 + t0 + 16 * b)] = b ? cmul(v[h * 8 + b], p8[b]) : v[h * 8];
  uint32_t wa[16], wb[16];
#pragma unroll
  for (int m = 0; m < 16; m++) {
    wa[m] = __ldcg(&g_wt[k * S_LEN + t + 128 * m]);
    wb[m] = __ldcg(&g_wt[(512 - k) * S_LEN + ((2048 - t - 128 * m) & 2047)]);
  }
  bar_sync(1 + half, 128);
  const int base3 = (t & 15) * 128 + (t >> 4) * 16;
#pragma unroll
  for (int i = 0; i < 16; i++) v[i] = my[f2_pad(base3 + i)];
  fft_reg<16, -1>(v);
  bar_sync(1 + half, 128);
#pragma unroll
  for (int m = 0; m < 16; m++) my[t + 128 * m] = v[m];
  __syncthreads();
  {
    float sn, cs;
    sincospif((float)k / 512.f, &sn, &cs);
    const float sc = 0.5f / (2048.f * 512.f);
#pragma unroll
    for (int m = 0; m < 16; m++) {
      const int j = t + 128 * m, jm = (2048 - j) & 2047;
      float2 A = unpack_bf16(wa[m]), B = unpack_bf16(wb[m]);
      B.y = -B.y;
      if (k == 0) {
        const float2 A2 = unpack_bf16(__ldcg(&g_wt[jm])), B2 = unpack_bf16(__ldcg(&g_wt[512 * S_LEN + j]));
        A = make_float2(0.5f * (A.x + A2.x), 0.5f * (A.y - A2.y));
        B = make_float2(0.5f * (B.x + B2.x), 0.5f * (B.y + B2.y));
      }
      const float2 df = make_float2((A.x - B.x) * sc, (A.y - B.y) * sc);
      const float2 ca = make_float2(fmaf(-sn, df.x, (A.x + B.x) * sc), fmaf(-sn, df.y, (A.y + B.y) * sc));
      const float2 cb = make_float2(-cs * df.y, cs * df.x);
      float2 zc = mir[jm];
      zc.y = -zc.y;
      const float2 r1 = cmul(ca, v[m]), r2 = cmul(cb, zc);
      v[m] = make_float2(r1.x + r2.x, r1.y + r2.y);
    }
  }
  fft_reg<16, 1>(v);
  __syncthreads();
#pragma unroll
  for (int i = 0; i < 16; i++) my[f2_pad(base3 + i)] = v[i];
  bar_sync(1 + half, 128);
#pragma unroll
  for (int h = 0; h < 2; h++) {
#pragma unroll
    for (int b = 0; b < 8; b++) {
      const float2 z = my[f2_pad((2 * kp + h) * 128 + t0 + 16 * b)];
      v[h * 8 + b] = b ? cmul(z, make_float2(p8[b].x, -p8[b].y)) : z;
    }
    fft_reg<8, 1>(v + h * 8);
#pragma unroll
    for (int b = 0; b < 8; b++) my[f2_pad((2 * kp + h) * 128 + t0 + 16 * b)] = v[h * 8 + b];
  }
  bar_sync(1 + half, 128);
#pragma unroll
  for (int i = 0; i < 16; i++) v[i] = my[f2_pad(i * 128 + t)];
  twiddle<16>(v, (float)t / 1024.f);
  fft_reg<16, 1>(v);
#pragma unroll
  for (int a = 0; a < 16; a++) g_z2[k * S_LEN + t + 128 * a] = pack_bf16(v[a].x, v[a].y);
}

__device__ __forceinline__ void fft_rows_inv(float2* fs, int item, bf16* __restrict__ out) {
  const int tid = threadIdx.x, s0 = item * 16;
  {
    const int row = tid & 15, k2 = tid >> 4;
    float2 v[32];
#pragma unroll
    for (int i = 0; i < 32; i++) v[i] = unpack_bf16(__ldcg(&g_z2[(k2 + 16 * i) * S_LEN + s0 + row]));
    fft_reg<32, 1>(v);
#pragma unroll
    for (int i = 0; i < 32; i++) fs[row * F1_LD + k2 * 33 + (i >> 1) + (i & 1) * 16] = v[i];
  }
  __syncthreads();
  {
    const int row = tid >> 4, t = tid & 15;
    const float2* d = fs + row * F1_LD + t;
    float2 a[16], b[16];
#pragma unroll
    for (int i = 0; i < 16; i++) { a[i] = d[i * 33]; b[i] = d[i * 33 + 16]; }
    twiddle<16>(a, (float)(2 * t) / 256.f); fft_reg<16, 1>(a);
    twiddle<16>(b, (float)(2 * t + 1) / 256.f); fft_reg<16, 1>(b);
    uint2* dst = reinterpret_cast<uint2*>(out + (size_t)(s0 + row) * OUT_LD) + t;
#pragma unroll
    for (int i = 0; i < 16; i++) dst[i * 16] = make_uint2(pack_bf16(a[i].x, a[i].y), pack_bf16(b[i].x, b[i].y));
  }
}

__global__ void __maxnreg__(112) fft_all(const bf16* __restrict__ x, const bf16* __restrict__ wr, const bf16* __restrict__ wi, bf16* __restrict__ out) {
  extern __shared__ float2 fs[];
  volatile int& s_item = *reinterpret_cast<volatile int*>(fs + 15 * F1_LD + 14 * 33 + 32);
  asm volatile("griddepcontrol.launch_dependents;" ::: "memory");
  int* ctr = &g_rings.ctr[0][0];
  int phase = 0, cnt = 0;
  for (;;) {
    __syncthreads();
    if (threadIdx.x == 0) {
      const int it = atomicAdd(ctr, 1) + 1;
      const int ph = (it >= 128) + (it >= 384) + (it >= 512);
      if (ph != phase) {
        if (cnt) { __threadfence(); atomicAdd(ctr + 32 + phase * 32, cnt); }
        const int target = ph == 1 ? 127 : 255;
        for (int i = 0; ph < 3 && i < (1 << 22); i++) {
          int v; asm volatile("ld.acquire.gpu.global.s32 %0, [%1];" : "=r"(v) : "l"(ctr + ph * 32) : "memory");
          if (v == target) break;
          __nanosleep(100);
        }
        phase = ph; cnt = 0;
      }
      cnt += ph < 2;
      if (it == 128) STAMP(5);
      if (it == 384) STAMP(6);
      if (it >= 512) STAMP(7);
      s_item = it;
    }
    __syncthreads();
    const int it = s_item;
    if (it >= 512) break;
    if (it < 128) {
      const int nx = it + (int)gridDim.x;
      if (nx < 128) {
        asm volatile("prefetch.global.L2 [%0];" ::"l"(x + (size_t)nx * 16 * DM + threadIdx.x * 64));
        asm volatile("prefetch.global.L2 [%0];" ::"l"((threadIdx.x < 128 ? wr : wi) + (size_t)nx * 16 * 513 + (threadIdx.x & 127) * 64));
      }
      fft_rows_fwd(fs, it, x, wr, wi);
    }
    else if (it < 384) fft_cols(fs, it - 128);
    else fft_rows_inv(fs, it - 384, out);
  }
  if (blockIdx.x == 0) asm volatile("griddepcontrol.wait;" ::: "memory");
}

typedef CUresult (*EncodeFn)(CUtensorMap*, CUtensorMapDataType, cuuint32_t, void*, const cuuint64_t*, const cuuint64_t*,
                             const cuuint32_t*, const cuuint32_t*, CUtensorMapInterleave, CUtensorMapSwizzle,
                             CUtensorMapL2promotion, CUtensorMapFloatOOBfill);
static EncodeFn g_encode;
static bool g_big;
static CUtensorMap make_map(const void* p, uint64_t cols, uint64_t rows, uint64_t ld, uint32_t bc, uint32_t br, bool swz) {
  CUtensorMap m;
  cuuint64_t dims[2] = {cols, rows}, st[1] = {ld * 2};
  cuuint32_t box[2] = {bc, br}, es[2] = {1, 1};
  g_encode(&m, CU_TENSOR_MAP_DATA_TYPE_BFLOAT16, 2, const_cast<void*>(p), dims, st, box, es, CU_TENSOR_MAP_INTERLEAVE_NONE,
           swz ? CU_TENSOR_MAP_SWIZZLE_128B : CU_TENSOR_MAP_SWIZZLE_NONE, CU_TENSOR_MAP_L2_PROMOTION_L2_256B,
           CU_TENSOR_MAP_FLOAT_OOB_FILL_NONE);
  return m;
}
template <typename... KA, typename... A>
static void launch(void (*k)(KA...), dim3 grid, dim3 block, size_t smem, int cluster, bool pdl, cudaStream_t st, A... args) {
  cudaLaunchConfig_t cfg = {};
  cfg.gridDim = grid; cfg.blockDim = block; cfg.dynamicSmemBytes = smem; cfg.stream = st;
  cudaLaunchAttribute at[2]; int n = 0;
  if (cluster > 1) { at[n].id = cudaLaunchAttributeClusterDimension; at[n].val.clusterDim.x = cluster; at[n].val.clusterDim.y = 1; at[n].val.clusterDim.z = 1; n++; }
  if (pdl) { at[n].id = cudaLaunchAttributeProgrammaticStreamSerialization; at[n].val.programmaticStreamSerializationAllowed = 1; n++; }
  cfg.attrs = at; cfg.numAttrs = n;
  cudaLaunchKernelEx(&cfg, k, args...);
}
#define PARAM(n, d) (d)

#define ACS 8
#define VCS 8
extern "C" void kernel_launch(void* const* d_in, const int* in_sizes, int n_in, void* d_out, int out_size) {
  const bf16* Ax = (const bf16*)d_in[0]; const bf16* Awr = (const bf16*)d_in[1]; const bf16* Awi = (const bf16*)d_in[2];
  const bf16* Bx = (const bf16*)d_in[3]; const bf16* mem0 = (const bf16*)d_in[4];
  const bf16* Wq = (const bf16*)d_in[5]; const bf16* Wk = (const bf16*)d_in[6]; const bf16* Wv = (const bf16*)d_in[7];
  const bf16* Wo = (const bf16*)d_in[8];
  bf16* out = (bf16*)d_out;
  if (!g_encode) {
    cudaDriverEntryPointQueryResult qr;
    cudaGetDriverEntryPoint("cuTensorMapEncodeTiled", (void**)&g_encode, cudaEnableDefault, &qr);
    cudaFuncSetAttribute(gemm_kernel, cudaFuncAttributeMaxDynamicSharedMemorySize, G_SMEM);
    cudaFuncSetAttribute(qk_kernel<2>, cudaFuncAttributeMaxDynamicSharedMemorySize, A_SMEM);
    cudaFuncSetAttribute(qk_kernel<ACS>, cudaFuncAttributeMaxDynamicSharedMemorySize, A_SMEM);
    cudaFuncSetAttribute(vo_kernel<VCS>, cudaFuncAttributeMaxDynamicSharedMemorySize, V_SMEM);
    cudaFuncSetAttribute(vo_kernel<2>, cudaFuncAttributeMaxDynamicSharedMemorySize, V_SMEM);
    cudaLaunchConfig_t cfg = {};
    cfg.gridDim = dim3(64); cfg.blockDim = dim3(256); cfg.dynamicSmemBytes = V_SMEM;
    cudaLaunchAttribute at;
    at.id = cudaLaunchAttributeClusterDimension; at.val.clusterDim.x = VCS; at.val.clusterDim.y = 1; at.val.clusterDim.z = 1;
    cfg.attrs = &at; cfg.numAttrs = 1;
    int n = 0;
    g_big = cudaOccupancyMaxActiveClusters(&n, vo_kernel<VCS>, &cfg) == cudaSuccess && n * VCS >= 120;
    cudaFuncSetAttribute(fft_all, cudaFuncAttributeMaxDynamicSharedMemorySize, F1_SMEM);
  }
  void *p_ux, *p_rings, *p_win;
  cudaGetSymbolAddress(&p_ux, g_ux); cudaGetSymbolAddress(&p_rings, g_rings); cudaGetSymbolAddress(&p_win, g_win);
  char* win = (char*)(((uintptr_t)p_win + (2u << 20) - 1) & ~(uintptr_t)((2u << 20) - 1));
  const CUtensorMap rWq = make_map(Wq, HD, DM, HD, 64, 128, true), rWk = make_map(Wk, HD, DM, HD, 64, 128, true),
                    rWv = make_map(Wv, HD, DM, HD, 64, 128, true), rWo = make_map(Wo, DM, HD, DM, 32, 128, false);
  CUtensorMap rX[3];
  for (int i = 0; i < 3; i++) {
    cuuint64_t dims[3] = {64, S_LEN, 16}, st[2] = {DM * 2, 128};
    cuuint32_t box[3] = {64, 32, i == 0 ? 4u : i == 1 ? 8u / VCS : 8u / ACS}, es[3] = {1, 1, 1};
    g_encode(&rX[i], CU_TENSOR_MAP_DATA_TYPE_BFLOAT16, 3, const_cast<bf16*>(Bx), dims, st, box, es, CU_TENSOR_MAP_INTERLEAVE_NONE,
             CU_TENSOR_MAP_SWIZZLE_128B, CU_TENSOR_MAP_L2_PROMOTION_L2_256B, CU_TENSOR_MAP_FLOAT_OOB_FILL_NONE);
  }
  const CUtensorMap mU = make_map(p_ux, HD, S_LEN, HD, 64, 64, true), mWo = make_map(Wo, DM, HD, DM, 64, 64, true);
  const CUtensorMap sU = make_map(p_ux, HD, S_LEN, HD, 64, 8, true);
  const CUtensorMap mOut = make_map(out, OUT_LD, S_LEN, OUT_LD, 64, 64, true);
  cudaStream_t st = cudaStreamPerThread;
  const Pace pace = {5 * PARAM("DU", 2950), 5 * PARAM("DM", 2020), 5 * PARAM("DOK", 140), 5 * PARAM("DL", 800), 5 * PARAM("DS", 100), 5 * PARAM("DC", 800)};
  if (g_big) launch(vo_kernel<VCS>, dim3(64), dim3(256), V_SMEM, VCS, false, st, rWv, rWo, rX[1], sU, mem0, Bx, win, pace, 0);
  else launch(vo_kernel<2>, dim3(64), dim3(256), V_SMEM, 2, false, st, rWv, rWo, rX[0], sU, mem0, Bx, win, pace, 0);
  const int nbig = g_big && ACS > 2 ? 56 : 0;
  if (nbig) launch(qk_kernel<ACS>, dim3(nbig), dim3(256), A_SMEM, ACS, true, st, rWq, rWk, rX[2], win, pace, 0, 0);
  launch(qk_kernel<2>, dim3(64 - nbig), dim3(256), A_SMEM, 2, true, st, rWq, rWk, rX[0], win, pace, 0, nbig);
  if (PARAM("BG", 8)) launch(fft_all, dim3(PARAM("BG", 8)), dim3(256), F1_SMEM, 1, true, st, Ax, Awr, Awi, out);
  launch(gemm_kernel, dim3(8, 16), dim3(288), G_SMEM, 2, true, st, mU, mWo, mWo, mWo, mOut, 8, 64, 1024, (const int*)((char*)p_rings + offsetof(Rings, ctr) + 3 * 128));
  if (PARAM("TAIL", 128)) launch(fft_all, dim3(PARAM("TAIL", 128)), dim3(256), F1_SMEM, 1, true, st, Ax, Awr, Awi, out);
}
```

```cpp
#include <cuda_runtime.h>
#include <cuda_bf16.h>
#include <cuda.h>
#include <stdint.h>

typedef __nv_bfloat16 bf16;

constexpr int S_LEN = 2048, DM = 1024, NH = 32, DH = 128, HD = 4096, NMEM = 8, SEG = 32, NSEG = 64;
constexpr int OUT_LD = 2048;
constexpr uint32_t SENT = 0xFFFFFFFFu;

__device__ __forceinline__ uint32_t smem_u32(const void* p) { return (uint32_t)__cvta_generic_to_shared(p); }
__device__ __forceinline__ void mbar_init(uint32_t bar, uint32_t cnt) {
  asm volatile("mbarrier.init.shared::cta.b64 [%0], %1;" ::"r"(bar), "r"(cnt) : "memory");
}
__device__ __forceinline__ void mbar_expect_tx(uint32_t bar, uint32_t bytes) {
  asm volatile("mbarrier.arrive.expect_tx.shared::cta.b64 _, [%0], %1;" ::"r"(bar), "r"(bytes) : "memory");
}
__device__ __forceinline__ void mbar_arrive(uint32_t bar) {
  asm volatile("mbarrier.arrive.shared::cta.b64 _, [%0];" ::"r"(bar) : "memory");
}
__device__ __forceinline__ void mbar_arrive_tx_if(uint32_t bar, uint32_t bytes, uint32_t cond) {
  asm volatile("{.reg .pred q; setp.ne.u32 q, %2, 0; @q mbarrier.arrive.expect_tx.shared::cta.b64 _, [%0], %1;}" ::"r"(bar), "r"(bytes), "r"(cond) : "memory");
}
__device__ __forceinline__ void mbar_arrive_cluster(uint32_t bar_cluster_addr) {
  asm volatile("mbarrier.arrive.shared::cluster.b64 _, [%0];" ::"r"(bar_cluster_addr) : "memory");
}
__device__ __forceinline__ bool mbar_try(uint32_t bar, uint32_t par) {
  uint32_t ok;
  asm volatile("{.reg .pred p; mbarrier.try_wait.parity.shared::cta.b64 p, [%1], %2; selp.u32 %0, 1, 0, p;}"
               : "=r"(ok) : "r"(bar), "r"(par) : "memory");
  return ok;
}
#define FAIL(id) do { asm volatile("trap; exit;"); __builtin_unreachable(); } while (0)
__device__ __forceinline__ void mbar_wait(uint32_t bar, uint32_t par) {
  if (__builtin_expect(!mbar_try(bar, par), 0)) {
    int it = 0;
    while (!mbar_try(bar, par)) { if (++it > (1 << 18)) FAIL((bar & 255) + par * 1000); }
  }
}
__device__ __forceinline__ void tma2d(uint32_t dst, const CUtensorMap* tm, int c0, int c1, uint32_t bar) {
  asm volatile("cp.async.bulk.tensor.2d.shared::cluster.global.mbarrier::complete_tx::bytes [%0], [%1, {%3, %4}], [%2];"
               ::"r"(dst), "l"(tm), "r"(bar), "r"(c0), "r"(c1) : "memory");
}
__device__ __forceinline__ void tma2d_ef(uint32_t dst, const CUtensorMap* tm, int c0, int c1, uint32_t bar) {
  asm volatile("cp.async.bulk.tensor.2d.shared::cluster.global.mbarrier::complete_tx::bytes.L2::cache_hint [%0], [%1, {%3, %4}], [%2], %5;"
               ::"r"(dst), "l"(tm), "r"(bar), "r"(c0), "r"(c1), "l"(0x12F0000000000000ull) : "memory");
}
__device__ __forceinline__ void tma2d_pf(const CUtensorMap* tm, int c0, int c1) {
  asm volatile("cp.async.bulk.prefetch.tensor.2d.L2.global [%0, {%1, %2}];" ::"l"(tm), "r"(c0), "r"(c1) : "memory");
}
__device__ __forceinline__ void tma2d_mc(uint32_t dst, const CUtensorMap* tm, int c0, int c1, uint32_t bar, uint16_t mask) {
  asm volatile("cp.async.bulk.tensor.2d.shared::cluster.global.mbarrier::complete_tx::bytes.multicast::cluster [%0], [%1, {%3, %4}], [%2], %5;"
               ::"r"(dst), "l"(tm), "r"(bar), "r"(c0), "r"(c1), "h"(mask) : "memory");
}
__device__ __forceinline__ void tma2d_store(const CUtensorMap* tm, uint32_t src, int c0, int c1) {
  asm volatile("cp.async.bulk.tensor.2d.global.shared::cta.bulk_group [%0, {%2, %3}], [%1];"
               ::"l"(tm), "r"(src), "r"(c0), "r"(c1) : "memory");
}
__device__ __forceinline__ uint32_t mapa(uint32_t a, uint32_t r) {
  uint32_t o; asm("mapa.shared::cluster.u32 %0, %1, %2;" : "=r"(o) : "r"(a), "r"(r)); return o;
}
__device__ __forceinline__ void st_async8(uint32_t addr, float a, float b, uint32_t bar) {
  asm volatile("st.async.weak.shared::cluster.mbarrier::complete_tx::bytes.v2.f32 [%0], {%1, %2}, [%3];"
               ::"r"(addr), "f"(a), "f"(b), "r"(bar) : "memory");
}
__device__ __forceinline__ void st_async8_if(uint32_t addr, float a, float b, uint32_t bar, uint32_t cond) {
  asm volatile("{.reg .pred q; setp.ne.u32 q, %4, 0; @q st.async.weak.shared::cluster.mbarrier::complete_tx::bytes.v2.f32 [%0], {%1, %2}, [%3];}"
               ::"r"(addr), "f"(a), "f"(b), "r"(bar), "r"(cond) : "memory");
}
__device__ __forceinline__ void st_async16(uint32_t addr, const float* v, uint32_t bar) {
  asm volatile("st.async.weak.shared::cluster.mbarrier::complete_tx::bytes.v4.f32 [%0], {%1, %2, %3, %4}, [%5];"
               ::"r"(addr), "f"(v[0]), "f"(v[1]), "f"(v[2]), "f"(v[3]), "r"(bar) : "memory");
}
__device__ __forceinline__ void st_async4(uint32_t addr, float a, uint32_t bar) {
  asm volatile("st.async.weak.shared::cluster.mbarrier::complete_tx::bytes.f32 [%0], %1, [%2];"
               ::"r"(addr), "f"(a), "r"(bar) : "memory");
}
__device__ __forceinline__ void cluster_sync() {
  asm volatile("barrier.cluster.arrive.release.aligned; barrier.cluster.wait.acquire.aligned;" ::: "memory");
}
__device__ __forceinline__ void bar_sync(int id, int n) { asm volatile("bar.sync %0, %1;" ::"r"(id), "r"(n) : "memory"); }
__device__ __forceinline__ void ldsm4(uint32_t& r0, uint32_t& r1, uint32_t& r2, uint32_t& r3, uint32_t a) {
  asm volatile("ldmatrix.sync.aligned.m8n8.x4.shared.b16 {%0,%1,%2,%3}, [%4];"
               : "=r"(r0), "=r"(r1), "=r"(r2), "=r"(r3) : "r"(a) : "memory");
}
__device__ __forceinline__ void ldsm4t(uint32_t& r0, uint32_t& r1, uint32_t& r2, uint32_t& r3, uint32_t a) {
  asm volatile("ldmatrix.sync.aligned.m8n8.x4.trans.shared.b16 {%0,%1,%2,%3}, [%4];"
               : "=r"(r0), "=r"(r1), "=r"(r2), "=r"(r3) : "r"(a) : "memory");
}
__device__ __forceinline__ void stsm4(uint32_t a, uint32_t r0, uint32_t r1, uint32_t r2, uint32_t r3) {
  asm volatile("stmatrix.sync.aligned.m8n8.x4.shared.b16 [%0], {%1,%2,%3,%4};"
               ::"r"(a), "r"(r0), "r"(r1), "r"(r2), "r"(r3) : "memory");
}
__device__ __forceinline__ void stsm1(uint32_t a, uint32_t r0) {
  asm volatile("stmatrix.sync.aligned.m8n8.x1.shared.b16 [%0], {%1};" ::"r"(a), "r"(r0) : "memory");
}
__device__ __forceinline__ void mma16816(float* d, uint32_t a0, uint32_t a1, uint32_t a2, uint32_t a3, uint32_t b0, uint32_t b1) {
  asm volatile("mma.sync.aligned.m16n8k16.row.col.f32.bf16.bf16.f32 {%0,%1,%2,%3}, {%4,%5,%6,%7}, {%8,%9}, {%0,%1,%2,%3};"
               : "+f"(d[0]), "+f"(d[1]), "+f"(d[2]), "+f"(d[3])
               : "r"(a0), "r"(a1), "r"(a2), "r"(a3), "r"(b0), "r"(b1));
}
__device__ __forceinline__ void mma1688(float* d, uint32_t a0, uint32_t a1, uint32_t b0) {
  asm volatile("mma.sync.aligned.m16n8k8.row.col.f32.bf16.bf16.f32 {%0,%1,%2,%3}, {%4,%5}, {%6}, {%0,%1,%2,%3};"
               : "+f"(d[0]), "+f"(d[1]), "+f"(d[2]), "+f"(d[3]) : "r"(a0), "r"(a1), "r"(b0));
}
__device__ __forceinline__ uint32_t pack_bf16(float lo, float hi) {
  uint32_t r; asm("cvt.rn.bf16x2.f32 %0, %1, %2;" : "=r"(r) : "f"(hi), "f"(lo)); return r;
}
__device__ __forceinline__ uint4 ld_relaxed16(const void* p) {
  uint4 v;
  asm volatile("ld.relaxed.gpu.global.v4.u32 {%0,%1,%2,%3}, [%4];" : "=r"(v.x), "=r"(v.y), "=r"(v.z), "=r"(v.w) : "l"(p) : "memory");
  return v;
}
__device__ __forceinline__ uint4 ld_relaxed16b(const void* p) {
  uint4 v;
  asm volatile("ld.relaxed.gpu.global.v4.b32 {%0,%1,%2,%3}, [%4];" : "=r"(v.x), "=r"(v.y), "=r"(v.z), "=r"(v.w) : "l"(p) : "memory");
  return v;
}
__device__ __forceinline__ void ld_relaxed16_if(uint4& v, const void* p, uint32_t cond) {
  asm volatile("{.reg .pred q; setp.ne.u32 q, %5, 0; @q ld.relaxed.gpu.global.v4.u32 {%0,%1,%2,%3}, [%4];}"
               : "+r"(v.x), "+r"(v.y), "+r"(v.z), "+r"(v.w) : "l"(p), "r"(cond) : "memory");
}
__device__ __forceinline__ void ld_relaxed8_if(uint2& v, const void* p, uint32_t cond) {
  asm volatile("{.reg .pred q; setp.ne.u32 q, %3, 0; @q ld.relaxed.gpu.global.v2.u32 {%0,%1}, [%2];}" : "+r"(v.x), "+r"(v.y) : "l"(p), "r"(cond) : "memory");
}
__device__ __forceinline__ uint32_t ld_relaxed4(const void* p) {
  uint32_t v; asm volatile("ld.relaxed.gpu.global.u32 %0, [%1];" : "=r"(v) : "l"(p) : "memory"); return v;
}
__device__ __forceinline__ void st_relaxed4(void* p, uint32_t v) {
  asm volatile("st.relaxed.gpu.global.u32 [%0], %1;" ::"l"(p), "r"(v) : "memory");
}
__device__ __forceinline__ void st_relaxed4_if(void* p, uint32_t v, uint32_t cond) {
  asm volatile("{.reg .pred q; setp.ne.u32 q, %2, 0; @q st.relaxed.gpu.global.u32 [%0], %1;}" ::"l"(p), "r"(v), "r"(cond) : "memory");
}
__device__ __forceinline__ void sts16(uint32_t a, uint4 v) {
  asm volatile("st.shared.v4.u32 [%0], {%1,%2,%3,%4};" ::"r"(a), "r"(v.x), "r"(v.y), "r"(v.z), "r"(v.w) : "memory");
}
__device__ __forceinline__ void sts4f(uint32_t a, float v) { asm volatile("st.shared.f32 [%0], %1;" ::"r"(a), "f"(v) : "memory"); }
__device__ __forceinline__ void sts8f(uint32_t a, float x, float y) { asm volatile("st.shared.v2.f32 [%0], {%1,%2};" ::"r"(a), "f"(x), "f"(y) : "memory"); }
__device__ __forceinline__ float lds4f(uint32_t a) { float v; asm volatile("ld.shared.f32 %0, [%1];" : "=f"(v) : "r"(a) : "memory"); return v; }
__device__ __forceinline__ float2 lds8f(uint32_t a) { float2 v; asm volatile("ld.shared.v2.f32 {%0,%1}, [%2];" : "=f"(v.x), "=f"(v.y) : "r"(a) : "memory"); return v; }
__device__ __forceinline__ uint32_t lds4(uint32_t a) { uint32_t v; asm volatile("ld.shared.u32 %0, [%1];" : "=r"(v) : "r"(a) : "memory"); return v; }
__device__ __forceinline__ uint2 lds8(uint32_t a) { uint2 v; asm volatile("ld.shared.v2.u32 {%0,%1}, [%2];" : "=r"(v.x), "=r"(v.y) : "r"(a) : "memory"); return v; }
__device__ __forceinline__ uint32_t umax4(uint4 v) { return max(max(v.x, v.y), max(v.z, v.w)); }
__device__ __forceinline__ float ex2(float x) { float y; asm("ex2.approx.ftz.f32 %0, %1;" : "=f"(y) : "f"(x)); return y; }

__device__ __forceinline__ void fence_gpu() { asm volatile("fence.acq_rel.gpu;" ::: "memory"); }
#define WG_FENCE() asm volatile("wgmma.fence.sync.aligned;" ::: "memory")
#define WG_COMMIT() asm volatile("wgmma.commit_group.sync.aligned;" ::: "memory")
#define WG_WAIT(n) asm volatile("wgmma.wait_group.sync.aligned " #n ";" ::: "memory")
__device__ __forceinline__ uint64_t mk_desc(uint32_t addr, uint32_t lbo, uint32_t sbo) {
  return (uint64_t)((addr >> 4) & 0x3FFF) | ((uint64_t)(lbo >> 4) << 16) | ((uint64_t)(sbo >> 4) << 32) | ((uint64_t)1 << 62);
}
__device__ __forceinline__ void stsm4t(uint32_t a, uint32_t r0, uint32_t r1, uint32_t r2, uint32_t r3) {
  asm volatile("stmatrix.sync.aligned.m8n8.x4.trans.shared.b16 [%0], {%1,%2,%3,%4};"
               ::"r"(a), "r"(r0), "r"(r1), "r"(r2), "r"(r3) : "memory");
}
__device__ __forceinline__ void sts16f(uint32_t a, float x, float y, float z, float w) {
  asm volatile("st.shared.v4.f32 [%0], {%1,%2,%3,%4};" ::"r"(a), "f"(x), "f"(y), "f"(z), "f"(w) : "memory");
}
__device__ __forceinline__ float4 lds16f(uint32_t a) {
  float4 v; asm volatile("ld.shared.v4.f32 {%0,%1,%2,%3}, [%4];" : "=f"(v.x), "=f"(v.y), "=f"(v.z), "=f"(v.w) : "r"(a) : "memory"); return v;
}
__device__ __forceinline__ uint4 lds16(uint32_t a) {
  uint4 v; asm volatile("ld.shared.v4.u32 {%0,%1,%2,%3}, [%4];" : "=r"(v.x), "=r"(v.y), "=r"(v.z), "=r"(v.w) : "r"(a) : "memory"); return v;
}
__device__ __forceinline__ uint4 lds16v(uint32_t a) {
  uint4 v; asm volatile("ld.volatile.shared.v4.u32 {%0,%1,%2,%3}, [%4];" : "=r"(v.x), "=r"(v.y), "=r"(v.z), "=r"(v.w) : "r"(a) : "memory"); return v;
}
__device__ __forceinline__ uint32_t lds4v(uint32_t a) { uint32_t v; asm volatile("ld.volatile.shared.u32 %0, [%1];" : "=r"(v) : "r"(a) : "memory"); return v; }
__device__ __forceinline__ float4 lds16fv(uint32_t a) {
  float4 v; asm volatile("ld.volatile.shared.v4.f32 {%0,%1,%2,%3}, [%4];" : "=f"(v.x), "=f"(v.y), "=f"(v.z), "=f"(v.w) : "r"(a) : "memory"); return v;
}
__device__ __forceinline__ uint4 lds16c(uint32_t a) {
  uint4 v; asm volatile("ld.volatile.shared::cluster.v4.u32 {%0,%1,%2,%3}, [%4];" : "=r"(v.x), "=r"(v.y), "=r"(v.z), "=r"(v.w) : "r"(a) : "memory"); return v;
}
__device__ __forceinline__ uint2 lds8v(uint32_t a) {
  uint2 v; asm volatile("ld.volatile.shared.v2.u32 {%0,%1}, [%2];" : "=r"(v.x), "=r"(v.y) : "r"(a) : "memory"); return v;
}
__device__ __forceinline__ uint2 ld_relaxed8(const void* p) {
  uint2 v; asm volatile("ld.relaxed.gpu.global.v2.u32 {%0,%1}, [%2];" : "=r"(v.x), "=r"(v.y) : "l"(p) : "memory"); return v;
}
__device__ __forceinline__ void st_relaxed8(void* p, uint32_t a, uint32_t b) {
  asm volatile("st.relaxed.gpu.global.v2.u32 [%0], {%1,%2};" ::"l"(p), "r"(a), "r"(b) : "memory");
}
__device__ __forceinline__ void st_relaxed16(void* p, uint4 v) {
  asm volatile("st.relaxed.gpu.global.v4.u32 [%0], {%1,%2,%3,%4};" ::"l"(p), "r"(v.x), "r"(v.y), "r"(v.z), "r"(v.w) : "memory");
}
__device__ __forceinline__ void bar_arrive(int id, int n) { asm volatile("bar.arrive %0, %1;" ::"r"(id), "r"(n) : "memory"); }
template <typename T> __device__ __forceinline__ void keep32(T& x) { asm volatile("" : "+r"(x)); }
template <typename T> __device__ __forceinline__ void keep64(T& x) { asm volatile("" : "+l"(x)); }
#define ACC16(d) "+f"(d[0]), "+f"(d[1]), "+f"(d[2]), "+f"(d[3]), "+f"(d[4]), "+f"(d[5]), "+f"(d[6]), "+f"(d[7]), \
                 "+f"(d[8]), "+f"(d[9]), "+f"(d[10]), "+f"(d[11]), "+f"(d[12]), "+f"(d[13]), "+f"(d[14]), "+f"(d[15])
#define OUT16(d) "=f"(d[0]), "=f"(d[1]), "=f"(d[2]), "=f"(d[3]), "=f"(d[4]), "=f"(d[5]), "=f"(d[6]), "=f"(d[7]), \
                 "=f"(d[8]), "=f"(d[9]), "=f"(d[10]), "=f"(d[11]), "=f"(d[12]), "=f"(d[13]), "=f"(d[14]), "=f"(d[15])
template <int ACC> __device__ __forceinline__ void wg_rs32(float* d, const uint32_t* a, uint64_t db) {
  if (ACC == 2)
    asm volatile("wgmma.mma_async.sync.aligned.m64n32k16.f32.bf16.bf16 "
                 "{%0,%1,%2,%3,%4,%5,%6,%7,%8,%9,%10,%11,%12,%13,%14,%15}, {%16,%17,%18,%19}, %20, 0, 1, 1, 0;"
                 : ACC16(d) : "r"(a[0]), "r"(a[1]), "r"(a[2]), "r"(a[3]), "l"(db));
  else if (ACC)
    asm volatile("wgmma.mma_async.sync.aligned.m64n32k16.f32.bf16.bf16 "
                 "{%0,%1,%2,%3,%4,%5,%6,%7,%8,%9,%10,%11,%12,%13,%14,%15}, {%16,%17,%18,%19}, %20, 1, 1, 1, 0;"
                 : ACC16(d) : "r"(a[0]), "r"(a[1]), "r"(a[2]), "r"(a[3]), "l"(db));
  else
    asm volatile("wgmma.mma_async.sync.aligned.m64n32k16.f32.bf16.bf16 "
                 "{%0,%1,%2,%3,%4,%5,%6,%7,%8,%9,%10,%11,%12,%13,%14,%15}, {%16,%17,%18,%19}, %20, 0, 1, 1, 0;"
                 : OUT16(d) : "r"(a[0]), "r"(a[1]), "r"(a[2]), "r"(a[3]), "l"(db));
}
__device__ __forceinline__ void acc_fence16(float* d) { asm volatile("" : ACC16(d)::"memory"); }
__device__ __forceinline__ void wg_ss32(float* d, uint64_t da, uint64_t db) {
  asm volatile("wgmma.mma_async.sync.aligned.m64n32k16.f32.bf16.bf16 "
               "{%0,%1,%2,%3,%4,%5,%6,%7,%8,%9,%10,%11,%12,%13,%14,%15}, %16, %17, 1, 1, 1, 1, 0;"
               : ACC16(d) : "l"(da), "l"(db));
}
__device__ __forceinline__ void wg_ss32z(float* d, uint64_t da, uint64_t db) {
  asm volatile("wgmma.mma_async.sync.aligned.m64n32k16.f32.bf16.bf16 "
               "{%0,%1,%2,%3,%4,%5,%6,%7,%8,%9,%10,%11,%12,%13,%14,%15}, %16, %17, 0, 1, 1, 1, 0;"
               : OUT16(d) : "l"(da), "l"(db));
}

#define STAMP(i)

__device__ __forceinline__ void wgmma_m64n128_ss_tb(float* d, uint64_t da, uint64_t db) {
  asm volatile(
      "wgmma.mma_async.sync.aligned.m64n128k16.f32.bf16.bf16 "
      "{%0,%1,%2,%3,%4,%5,%6,%7,%8,%9,%10,%11,%12,%13,%14,%15,%16,%17,%18,%19,%20,%21,%22,%23,%24,%25,%26,%27,%28,%29,%30,%31,"
      "%32,%33,%34,%35,%36,%37,%38,%39,%40,%41,%42,%43,%44,%45,%46,%47,%48,%49,%50,%51,%52,%53,%54,%55,%56,%57,%58,%59,%60,%61,%62,%63},"
      "%64,%65,1,1,1,0,1;"
      : "+f"(d[0]), "+f"(d[1]), "+f"(d[2]), "+f"(d[3]), "+f"(d[4]), "+f"(d[5]), "+f"(d[6]), "+f"(d[7]), "+f"(d[8]), "+f"(d[9]),
        "+f"(d[10]), "+f"(d[11]), "+f"(d[12]), "+f"(d[13]), "+f"(d[14]), "+f"(d[15]), "+f"(d[16]), "+f"(d[17]), "+f"(d[18]), "+f"(d[19]),
        "+f"(d[20]), "+f"(d[21]), "+f"(d[22]), "+f"(d[23]), "+f"(d[24]), "+f"(d[25]), "+f"(d[26]), "+f"(d[27]), "+f"(d[28]), "+f"(d[29]),
        "+f"(d[30]), "+f"(d[31]), "+f"(d[32]), "+f"(d[33]), "+f"(d[34]), "+f"(d[35]), "+f"(d[36]), "+f"(d[37]), "+f"(d[38]), "+f"(d[39]),
        "+f"(d[40]), "+f"(d[41]), "+f"(d[42]), "+f"(d[43]), "+f"(d[44]), "+f"(d[45]), "+f"(d[46]), "+f"(d[47]), "+f"(d[48]), "+f"(d[49]),
        "+f"(d[50]), "+f"(d[51]), "+f"(d[52]), "+f"(d[53]), "+f"(d[54]), "+f"(d[55]), "+f"(d[56]), "+f"(d[57]), "+f"(d[58]), "+f"(d[59]),
        "+f"(d[60]), "+f"(d[61]), "+f"(d[62]), "+f"(d[63])
      : "l"(da), "l"(db));
}

constexpr int G_STAGES = 4;
constexpr int G_STAGE_BYTES = 32768;
constexpr int G_SMEM = G_STAGES * G_STAGE_BYTES + 128;

__global__ void __launch_bounds__(288, 2)
gemm_kernel(const __grid_constant__ CUtensorMap tmA, const __grid_constant__ CUtensorMap tmB0,
            const __grid_constant__ CUtensorMap tmB1, const __grid_constant__ CUtensorMap tmB2,
            const __grid_constant__ CUtensorMap tmC, int nb_per, int kblocks, int c_col0, const int* done) {
  extern __shared__ __align__(1024) uint8_t smem_raw[];
  const uint32_t sb = smem_u32(smem_raw);
  if (sb & 1023) __trap();
  const uint32_t bars = sb + G_STAGES * G_STAGE_BYTES;
  const int tid = threadIdx.x, wg = tid >> 7;
  asm volatile("griddepcontrol.launch_dependents;" ::: "memory");
  uint32_t rank; asm("mov.u32 %0, %%cluster_ctarank;" : "=r"(rank));
  const int nt = blockIdx.x, mt = blockIdx.y;
  const int bsel = nt / nb_per, n0 = (nt - bsel * nb_per) * 128;
  const CUtensorMap* tb = bsel == 0 ? &tmB0 : (bsel == 1 ? &tmB1 : &tmB2);
  if (tid == 256) {
    for (int i = 0; i < G_STAGES; i++) { mbar_init(bars + i * 8, 1); mbar_init(bars + (G_STAGES + i) * 8, 4); }
    asm volatile("fence.mbarrier_init.release.cluster;" ::: "memory");
    asm volatile("fence.proxy.async;" ::: "memory");
    for (int kb = 0; kb < G_STAGES; kb++) {
      const uint32_t b = sb + kb * G_STAGE_BYTES + 16384, fb = bars + kb * 8;
      mbar_expect_tx(fb, G_STAGE_BYTES);
      tma2d(b, tb, n0, kb * 64, fb);
      tma2d(b + 8192, tb, n0 + 64, kb * 64, fb);
    }
    for (int i = 0; i < (1 << 22); i++) {
      int v; asm volatile("ld.acquire.gpu.global.s32 %0, [%1];" : "=r"(v) : "l"(done) : "memory");
      if (v == 255) break;
    }
    asm volatile("fence.proxy.async;" ::: "memory");
  }
  __syncwarp();
  cluster_sync();
  if (wg == 2) {
    if (tid == 256) {
      STAMP(3);
      for (int kb = 0; kb < kblocks; kb++) {
        const int st = kb % G_STAGES, ph = (kb / G_STAGES) & 1;
        const uint32_t a = sb + st * G_STAGE_BYTES, b = a + 16384, fb = bars + st * 8;
        if (kb >= G_STAGES) { mbar_wait(bars + (G_STAGES + st) * 8, ph ^ 1); mbar_expect_tx(fb, G_STAGE_BYTES); }
        tma2d_mc(a + rank * 8192, &tmA, kb * 64, mt * 128 + rank * 64, fb, (uint16_t)3);
        if (kb >= G_STAGES) { tma2d(b, tb, n0, kb * 64, fb); tma2d(b + 8192, tb, n0 + 64, kb * 64, fb); }
      }
    }
  } else {
    const int cw = wg;
    float acc[64];
#pragma unroll
    for (int i = 0; i < 64; i++) acc[i] = 0.f;
    for (int kb = 0; kb < kblocks; kb++) {
      const int st = kb % G_STAGES, ph = (kb / G_STAGES) & 1;
      mbar_wait(bars + st * 8, ph);
      const uint32_t a = sb + st * G_STAGE_BYTES + cw * 8192, b = sb + st * G_STAGE_BYTES + 16384;
      const uint64_t da = mk_desc(a, 16, 1024), db = mk_desc(b, 8192, 1024);
      WG_FENCE();
#pragma unroll
      for (int k = 0; k < 4; k++) wgmma_m64n128_ss_tb(acc, da + k * 2, db + k * 128);
      WG_COMMIT();
      WG_WAIT(0);
      if (kb + G_STAGES < kblocks && (tid & 127) < 2) mbar_arrive_cluster(mapa(bars + (G_STAGES + st) * 8, tid & 1));
    }
    WG_WAIT(0);
    bar_sync(1, 256);
    const int w4 = (tid >> 5) & 3, lane = tid & 31;
    const uint32_t cbuf = sb + cw * 16384;
    const int row = w4 * 16 + (lane & 7) + ((lane >> 3) & 1) * 8;
#pragma unroll
    for (int j = 0; j < 8; j++) {
      const int chunk = (j & 3) * 2 + (lane >> 4);
      const uint32_t ad = cbuf + (j >> 2) * 8192 + row * 128 + ((chunk ^ (row & 7)) << 4);
      stsm4(ad, pack_bf16(acc[j * 8 + 0], acc[j * 8 + 1]), pack_bf16(acc[j * 8 + 2], acc[j * 8 + 3]),
            pack_bf16(acc[j * 8 + 4], acc[j * 8 + 5]), pack_bf16(acc[j * 8 + 6], acc[j * 8 + 7]));
    }
    asm volatile("fence.proxy.async.shared::cta;" ::: "memory");
    bar_sync(2 + cw, 128);
    if ((tid & 127) == 0) {
      tma2d_store(&tmC, cbuf, c_col0 + nt * 128, mt * 128 + cw * 64);
      tma2d_store(&tmC, cbuf + 8192, c_col0 + nt * 128 + 64, mt * 128 + cw * 64);
      asm volatile("cp.async.bulk.commit_group; cp.async.bulk.wait_group 0;" ::: "memory");
    }
  }
  __syncwarp();
  cluster_sync();
  if (tid == 0) STAMP(4);
  if (nt == 0 && mt == 0) asm volatile("griddepcontrol.wait;" ::: "memory");
}

__host__ __device__ constexpr uint32_t wpage(int L) {
  return (uint32_t)(((L & 1) << 18) | (((L >> 1) & 1) << 20) | (((L >> 2) & 1) << 13) | (((L >> 3) & 1) << 16) | (((L >> 4) & 1) << 17) |
                    (((L >> 5) & 1) << 19) | ((((L >> 2) ^ (L >> 3) ^ (L >> 4) ^ (L >> 5)) & 1) << 12));
}
constexpr int L_MEM = 0;
constexpr int L_U = 4;
constexpr int L_VM = 20;
constexpr int L_FLAG = 52;
constexpr int L_PROBE = 8;
constexpr int VX0 = 32768;
constexpr int EX_K = 4096, EX_CTA = 9216, EX_BYTES = 2 * EX_CTA;
struct Rings {
  uint32_t side[64];
  uint4 ex[4][NH * EX_BYTES / 16];
  int ctr[5][32];
};
__device__ Rings g_rings;
__device__ uint4 g_win[(4 << 20) / 16];
__device__ unsigned g_epoch;
__device__ bf16 g_ux[S_LEN * HD];
constexpr uint32_t TAG = 0x10000u;

constexpr int SB0 = 1024;
#define POLL_LIMIT (1 << 18)

#define TR(i)
#define TRB(i)
#define TRK(t)
#define TRD(c)
#define CNT(i)
#define LOGT(t)
#define ELECT "{.reg .pred p; elect.sync _|p, 0xffffffff; @p "

#define NPRE 2
#define GLA 3
#define CH4 0
#define GFEN 0
#define CHKN 3
#define HN 57
#define H0POS 0
#define LDM lds16v
#define PIN 0
#define H1POS 1
#define QC0 3
#define QC1 9
#define QC2 15
#define QC3 47
#define RESTART 500
#define FIRST 600
#define ALARM 700
#define EXPT 0
#define BACKOFF 200
#define VMPOS 0
#define MEMMC 0
#define CHPOS 1
#define CDEP 1
#define TKN 0
#define NPROBE 4
#define KEEP 1
#define LOOKD 150
#define WPF 0
#define METRO 0
#define BEATS 8
#define P14 7
#define P15 13
#define L14 2
#define L15 8
#define NB 99
#define CL 13
#define CK0 11
#define PINA 0
#define LN 14
#define QUIET 140
#define NEARBY 260
#define ZN 3
#define PACE 2
#define XQ 24
#define XS 8
#define BURST 0
#define ATT 1
#define XP 4
template <bool B> struct BoolC { static constexpr bool value = B; };
template <int N> struct IntC { static constexpr int value = N; };
template <typename T> __device__ __forceinline__ T* goff(T* base, uint32_t bytes) {
  return reinterpret_cast<T*>(reinterpret_cast<char*>(base) + bytes);
}
__device__ __forceinline__ char* other(char* p) { return reinterpret_cast<char*>(reinterpret_cast<uintptr_t>(p) ^ 4096); }
__device__ __forceinline__ uint2 ld_tagged8(const void* p) {
  uint2 v;
  asm volatile("{.reg .b64 t; ld.relaxed.gpu.global.b64 t, [%2]; mov.b64 {%0, %1}, t;}" : "=r"(v.x), "=r"(v.y) : "l"(p) : "memory");
  return v;
}
__device__ __forceinline__ uint32_t clk32() { unsigned long long t; asm volatile("mov.u64 %0, %%clock64;" : "=l"(t)::"memory"); return (uint32_t)t; }
__device__ __forceinline__ uint32_t gtime() { unsigned long long t; asm volatile("mov.u64 %0, %%globaltimer;" : "=l"(t)::"memory"); return (uint32_t)t; }
__device__ __forceinline__ uint32_t time_offset(uint32_t z) {
  const uint32_t g0 = gtime() * 9 + z;
  uint32_t a = g0 * -8;
  const uint32_t c0 = clk32();
#pragma unroll
  for (int i = 0; i < 8; i++)
    asm volatile("{.reg .u64 t; .reg .u32 l, h; mov.u64 t, %%globaltimer; mov.b64 {l, h}, t; mad.lo.u32 %0, l, 9, %0;}" : "+r"(a)::"memory");
  return g0 + (a >> 3) - c0 * 5 - (((clk32() - c0) * 5) >> 1);
}
__device__ __forceinline__ void spin_coarse(uint32_t t) {
  asm volatile("{.reg .pred p, q; .reg .u32 i, l, h; .reg .u64 c; .reg .s32 x; mov.u32 i, 0;\n"
               "LC: mov.u64 c, %%globaltimer; mov.b64 {l, h}, c; mad.lo.s32 x, l, 9, %0; add.u32 i, i, 1; setp.lt.u32 q, i, 4096;\n"
               "setp.lt.and.s32 p, x, 0, q; @p bra LC;}" ::"r"(-t) : "memory");
}
__device__ __forceinline__ void spin_until(uint32_t t, uint32_t tk) {
  const uint32_t d = tk - t;
  asm volatile("{.reg .pred p, q; .reg .u32 i, l, h; .reg .u64 c; .reg .s32 x; mov.u32 i, 0;\n"
               "LS: mov.u64 c, %%clock64; mov.b64 {l, h}, c; mad.lo.s32 x, l, 5, %0; add.u32 i, i, 1; setp.lt.u32 q, i, 4096;\n"
               "setp.lt.and.s32 p, x, 0, q; @p bra LS;}" ::"r"(d) : "memory");
}
__device__ __forceinline__ uint32_t approach(uint32_t t, uint32_t z) { spin_coarse(t - NEARBY * 5); return time_offset(z); }
struct Pace { int u0, m0, mu, mm, ok, late, dec, cap, s, c; };
__device__ __forceinline__ uint2 last_stores(uint4 f, const char* flags, int s) {
  for (int it = 0; __any_sync(~0u, ((f.x ^ s) | (f.y ^ s) | (f.z ^ s) | (f.w ^ s)) & 31); it++) {
    CNT(4);
    if (it) spin_until(clk32() * 5 + BACKOFF * 5, 0);
    f = ld_relaxed16(flags);
    if (it > POLL_LIMIT) FAIL(7000 + s);
  }
  const uint32_t now = gtime() * 9 + 65536;
  return make_uint2(now - __reduce_min_sync(~0u, min(now - f.x, now - f.y)), now - __reduce_min_sync(~0u, min(now - f.z, now - f.w)));
}
__device__ __forceinline__ int track(int e, int x, const Pace& d) { return max(min(x, e + d.cap), e - max(max(d.dec, (e - x) >> 2), e - x - d.cap)); }
__device__ __forceinline__ uint4 next_plan(uint4 p, uint2 l, int s, const Pace& d) {
  const bool late = (int)(l.x + d.ok - p.y) > 0 || s == 0;
  int eu = p.z, em = p.w & ~1;
  if (s && (int)(l.y + d.ok - p.x) <= 0) eu = track(eu, l.x - p.x, d);
  if (p.w & 1) em = track(em, l.y - p.x + em + d.mm, d) & ~1;
  const uint32_t tm = (late ? l.x + d.late : p.y) + em + d.mm;
  return make_uint4(tm, tm + eu + d.mu, eu, em | !late);
}
__device__ __forceinline__ const char* flag_ptr(const char* G, uint32_t near, uint32_t t16, int s) {
  keep32(t16);
  return reinterpret_cast<const char*>(reinterpret_cast<uintptr_t>(G + ((wpage(L_FLAG) ^ near) + (s & 1) * 512)) | (t16 & 0x1F0));
}
__device__ __forceinline__ void arrive_all(uint32_t CS, uint32_t t16, uint32_t off) {
  keep32(t16);
  const uint32_t l = (t16 >> 4) & 31;
  if (l < CS) mbar_arrive_cluster(mapa(SB0 + off, l));
  __syncwarp();
}
template <int N> __device__ __forceinline__ uint32_t idle(uint32_t z) {
#pragma unroll
  for (int i = 0; i < N; i++) asm volatile("mad.lo.u32 %0, %0, %0, %0;" : "+r"(z));
  return z;
}
__device__ __forceinline__ uint32_t junk() { uint32_t x; asm volatile("" : "=r"(x)); return x; }
__device__ __forceinline__ float rcp_fast(float x) { float y; asm("rcp.approx.ftz.f32 %0, %1;" : "=f"(y) : "f"(x)); return y; }
__device__ __forceinline__ void mma_z(float* d, uint32_t a0, uint32_t a1, uint32_t a2, uint32_t a3, uint32_t b0, uint32_t b1) {
  asm volatile("mma.sync.aligned.m16n8k16.row.col.f32.bf16.bf16.f32 {%0,%1,%2,%3}, {%4,%5,%6,%7}, {%8,%9}, {%10,%10,%10,%10};"
               : "=f"(d[0]), "=f"(d[1]), "=f"(d[2]), "=f"(d[3])
               : "r"(a0), "r"(a1), "r"(a2), "r"(a3), "r"(b0), "r"(b1), "f"(0.f));
}
__device__ __forceinline__ void mma1688z(float* d, uint32_t a0, uint32_t a1, uint32_t b0) {
  asm volatile("mma.sync.aligned.m16n8k8.row.col.f32.bf16.bf16.f32 {%0,%1,%2,%3}, {%4,%5}, {%6}, {%7,%7,%7,%7};"
               : "=f"(d[0]), "=f"(d[1]), "=f"(d[2]), "=f"(d[3]) : "r"(a0), "r"(a1), "r"(b0), "f"(0.f));
}
#define MMA_W(d, o, b0, b1) mma16816(d, w[o], w[(o) + 1], w[(o) + 2], w[(o) + 3], b0, b1)
#define MMA_X(d, x, b0, b1) mma16816(d, (x)[0], (x)[1], (x)[2], (x)[3], b0, b1)
#define MMA_XZ(d, x, b0, b1) mma_z(d, (x)[0], (x)[1], (x)[2], (x)[3], b0, b1)
__device__ __forceinline__ void ldw(uint32_t* x, uint32_t a) { ldsm4t(x[0], x[1], x[2], x[3], a); }
__device__ __forceinline__ void ldm(uint32_t* x, uint32_t a) { ldsm4(x[0], x[1], x[2], x[3], a); }
__device__ __forceinline__ void ldm_if(uint32_t* x, uint32_t a, uint32_t c) {
  asm volatile("{.reg .pred p; setp.ne.u32 p, %5, 0; @p ldmatrix.sync.aligned.m8n8.x4.shared.b16 {%0,%1,%2,%3}, [%4];}"
               : "=r"(x[0]), "=r"(x[1]), "=r"(x[2]), "=r"(x[3]) : "r"(a), "r"(c) : "memory");
}
__device__ __forceinline__ void bulk(uint32_t dst, const void* src, uint32_t n, uint32_t bar) {
  asm volatile(ELECT "cp.async.bulk.shared::cluster.global.mbarrier::complete_tx::bytes [%0], [%1], %2, [%3];}" ::"r"(dst), "l"(src), "r"(n), "r"(bar) : "memory");
}
template <uint32_t MASK> __device__ __forceinline__ void bulk_mc(uint32_t dst, const void* src, uint32_t n, uint32_t bar) {
  asm volatile(ELECT "cp.async.bulk.shared::cluster.global.mbarrier::complete_tx::bytes.multicast::cluster [%0], [%1], %2, [%3], %4;}"
               ::"r"(dst), "l"(src), "r"(n), "r"(bar), "h"((uint16_t)MASK) : "memory");
}
__device__ __forceinline__ void issue_x(const CUtensorMap* tm, uint32_t dst, uint32_t bar, int seg, int chunk, uint32_t mask) {
  asm volatile(ELECT "cp.async.bulk.tensor.3d.shared::cluster.global.mbarrier::complete_tx::bytes.multicast::cluster [%0], [%1, {%3, %4, %5}], [%2], %6;}"
               ::"r"(dst), "l"(tm), "r"(bar), "r"(0), "r"(seg * SEG), "r"(chunk), "h"((uint16_t)mask) : "memory");
}
__device__ __forceinline__ void expect(uint32_t bar, uint32_t bytes) {
  asm volatile(ELECT "mbarrier.arrive.expect_tx.shared::cta.b64 _, [%0], %1;}" ::"r"(bar), "r"(bytes) : "memory");
}
__device__ __forceinline__ void wait_ft(uint32_t bar, uint32_t par) {
  asm volatile("{.reg .pred p, q; .reg .u32 i; mov.u32 i, 0;\n"
               "LW: add.u32 i, i, 1; setp.lt.u32 q, i, 0x20000;\n"
               "mbarrier.try_wait.parity.shared::cta.b64 p, [%0], %1;\n"
               "not.pred p, p; and.pred q, q, p; @q bra LW;}" ::"r"(bar), "r"(par) : "memory");
}
__device__ __forceinline__ char* ptr64(uint32_t lo, uint32_t hi) { return reinterpret_cast<char*>(((uint64_t)hi << 32) | lo); }
__device__ __forceinline__ uint32_t plo(const void* p) { return (uint32_t)reinterpret_cast<uintptr_t>(p); }
__device__ __forceinline__ uint32_t phi(const void* p) { return (uint32_t)(reinterpret_cast<uintptr_t>(p) >> 32); }
__device__ __forceinline__ uint32_t pack_tag(float lo, float hi, uint32_t tg) {
  return ((__float_as_uint(hi) + (tg ^ TAG)) & 0xFFFE0000u) | pack_bf16(lo, __uint_as_float(tg));
}
__device__ __forceinline__ void st_tagged8(void* p, uint32_t a, uint32_t b) {
  asm volatile("{.reg .b64 t; mov.b64 t, {%1, %2}; st.relaxed.gpu.global.b64 [%0], t;}" ::"l"(p), "r"(a), "r"(b) : "memory");
}
__device__ __forceinline__ void st_tagged8_if(void* p, uint32_t a, uint32_t b, bool c) {
  asm volatile("{.reg .b64 t; .reg .pred q; setp.ne.u32 q, %3, 0; mov.b64 t, {%1, %2}; @q st.relaxed.gpu.global.b64 [%0], t;}" ::"l"(p), "r"(a), "r"(b), "r"((uint32_t)c) : "memory");
}
__device__ __forceinline__ void st_tagged16(void* p, uint4 v) {
  asm volatile("{.reg .b128 t; .reg .b64 a, b; mov.b64 a, {%1, %2}; mov.b64 b, {%3, %4}; mov.b128 t, {a, b}; st.relaxed.gpu.global.b128 [%0], t;}"
               ::"l"(p), "r"(v.x), "r"(v.y), "r"(v.z), "r"(v.w) : "memory");
}
__device__ __forceinline__ uint4 ld_tagged16(const void* p) {
  uint4 v;
  asm volatile("{.reg .b128 t; .reg .b64 a, b; ld.relaxed.gpu.global.b128 t, [%4]; mov.b128 {a, b}, t; mov.b64 {%0, %1}, a; mov.b64 {%2, %3}, b;}"
               : "=r"(v.x), "=r"(v.y), "=r"(v.z), "=r"(v.w) : "l"(p) : "memory");
  return v;
}
__device__ __forceinline__ void chk2(uint32_t& c, const uint4& v, uint32_t tg) {
  asm volatile("lop3.b32 %0, %0, %1, %3, 0xF6; lop3.b32 %0, %0, %2, %3, 0xF6;" : "+r"(c) : "r"(v.x), "r"(v.z), "r"(tg));
}
__device__ __forceinline__ void sched_fence(uint32_t zero, int n) {
  asm volatile("{.reg .pred p; setp.eq.u32 p, %0, %1; @p exit;}" ::"r"(zero), "r"(n + 1001) : "memory");
}
#define HERE(x) x |= clk32() & zero
__device__ __forceinline__ void pin(uint64_t& x, uint32_t zero) {
  asm volatile("{.reg .pred p; setp.ne.u32 p, %1, 0; @p mov.u64 %0, %%clock64;}" : "+l"(x) : "r"(zero) : "memory");
}
__device__ __forceinline__ void landed(uint32_t y) {
  asm volatile("{.reg .pred p; setp.ne.u32 p, %0, 0; vote.sync.any.pred p, p, 0xffffffff; @p exit;}" ::"r"(y) : "memory");
}
__device__ __forceinline__ uint64_t cdesc(uint32_t v, int off) {
  const uint32_t lo = v + (uint32_t)(((SB0 + off) >> 4) | (1 << 16));
  return ((uint64_t)0x40000040u << 32) | lo;
}
__device__ __forceinline__ uint64_t ndesc(uint32_t v, int off, int kstr, int mstr) {
  const uint32_t lo = v + (uint32_t)(((SB0 + off) >> 4) | ((kstr >> 4) << 16));
  return ((uint64_t)(mstr >> 4) << 32) | lo;
}
__device__ __forceinline__ constexpr int xk(int k) { return (k >> 2) * 4096 + (k & 3) * 32; }
constexpr uint32_t ONE2 = 0x3F803F80u;
constexpr float SCL = 0.08838834764831845f * 1.4426950408889634f;
__device__ __forceinline__ void exp10v(float* sc) {
  float ml = fmaxf(fmaxf(fmaxf(sc[0], sc[1]), fmaxf(sc[2], sc[3])), fmaxf(fmaxf(sc[4], sc[5]), fmaxf(sc[6], sc[7])));
  ml = fmaxf(ml, fmaxf(sc[8], sc[9]));
  const float m1 = __shfl_xor_sync(~0u, ml, 1), m2 = __shfl_xor_sync(~0u, ml, 2), m3 = __shfl_xor_sync(~0u, ml, 3);
  const float mo = fmaxf(fmaxf(ml, m1), fmaxf(m2, m3));
#pragma unroll
  for (int i = 0; i < 10; i++) sc[i] = ex2(sc[i] - mo);
}
#define UNI(x) __reduce_max_sync(~0u, (uint32_t)(x))
#define OPQ(x) __shfl_sync(~0u, (uint32_t)(x), lane)
#define BASES() uint32_t t16 = t16_; keep32(t16); const uint32_t l16 = t16 + wofs; (void)l16
__device__ __forceinline__ void probe_init(char* G, int id) {
  const int t = threadIdx.x;
  if (t < 32) *reinterpret_cast<uint4*>(G + ((wpage(L_PROBE + (id >> 5)) ^ ((t & 2) << 11)) + 16384 + ((id + (t >> 2)) & 31) * 128 + (t & 1) * 16)) = make_uint4(0, 0, 0, 0);
}
__device__ __forceinline__ void probe_near(char* G, int id, uint32_t dst) {
  unsigned* p0 = reinterpret_cast<unsigned*>(G + wpage(L_PROBE + (id >> 5)) + 16384 + (id & 31) * 128);
  unsigned best[2] = {~0u, ~0u};
#pragma unroll 2
  for (int i = 0; i < NPROBE; i++) {
    const unsigned t0 = clk32();
    const unsigned x = atomicExch(reinterpret_cast<unsigned*>(reinterpret_cast<uintptr_t>(p0) ^ ((i & 1) << 12)), (unsigned)i);
    asm volatile("{.reg .pred p; setp.eq.u32 p, %0, 0xffffffff; @p exit;}" ::"r"(x) : "memory");
    best[i & 1] = min(best[i & 1], clk32() - t0);
  }
  asm volatile("red.shared.min.u32 [%0], %1; red.shared.min.u32 [%0 + 4], %2;" ::"r"(dst), "r"(best[0]), "r"(best[1]) : "memory");
}
__device__ __forceinline__ uint32_t pick_near(uint32_t CS, uint32_t off) {
  uint32_t a, b;
  asm volatile("ld.shared::cluster.v2.u32 {%0, %1}, [%2];" : "=r"(a), "=r"(b) : "r"(mapa(SB0 + off, threadIdx.x & (CS - 1))) : "memory");
  return UNI(__reduce_min_sync(~0u, b) < __reduce_min_sync(~0u, a) ? 4096u : 0u);
}
__device__ __forceinline__ void start_arrive(uint32_t dst) {
  asm volatile("fence.proxy.async.global;" ::: "memory");
  __threadfence();
  sts4f(dst, __uint_as_float((atomicAdd(&g_epoch, 1u) & ~127u) + 128u));
}
__device__ __forceinline__ void start_wait(uint32_t src) {
  const unsigned target = lds4(src);
  for (int i = 0;; i++) {
    unsigned v; asm volatile("ld.acquire.gpu.global.u32 %0, [%1];" : "=r"(v) : "l"(&g_epoch) : "memory");
    if (__all_sync(~0u, (int)(v - target) >= 0) || i > (1 << 20)) break;
  }
}

template <int CS> __device__ __forceinline__ void fetch_mem_mc(uint32_t dst, const char* G, uint32_t off, int rank, uint32_t bar) {
  constexpr int PB = CS == 8 ? 2048 : 4096;
#pragma unroll
  for (int i = 0; i < 16384 / PB / CS; i++) {
    const uint32_t o = (rank * (16384 / PB / CS) + i) * PB;
    bulk_mc<(1u << CS) - 1>(dst + o, G + (off + ((o & 4096) << 6) + ((o & 8192) << 7) + (o & 4095)), PB, bar);
  }
}
template <int wg, int MEM, bool PRE, typename GV, typename W, typename F>
__device__ __forceinline__ void gemv_mem(GV& gv, const uint32_t* w, int s, uint32_t t16_, uint32_t wofs, uint32_t near, char* G, W wsa,
                                         uint32_t bar, uint32_t zero, uint32_t trc, F hook) {
  const uint32_t tg = (s & 1) << 16;
#pragma unroll 1
  for (;;) {
    BASES();
    const uint32_t mb = l16 + MEM + wg * 8192;
    if (PRE) landed(gv.prefetch(lds4(wsa(t16))) & zero);
    TR(14);
    wait_ft(bar, s & 1);
    TR(0);
    gv.first(mb);
    gv.c = 0;
    gv.tg = tg; gv.z0 = zero;
    bool bad;
    gv.template run<0, 16>(w, mb, [&](auto nc) __attribute__((always_inline)) {
      if (decltype(nc)::value == GV::CV) bad = __any_sync(~0u, gv.c & (s ? TAG : 0));
      hook(nc, bad);
    });
    if (__builtin_expect(!bad, 1)) break;
    CNT(MEM == 0x28000 ? 0 : 2);
    uint4 v[4];
    const char* src = G + (near + (wg << 20) + ((t16 - SB0) & 0x7F0));
    for (int it = 0;; it++) {
      uint32_t c = 0;
#pragma unroll
      for (int i = 0; i < 4; i++) v[i] = ld_tagged16(src + (i & 1) * 2048 + (i >> 1) * (1 << 18));
#pragma unroll
      for (int i = 0; i < 4; i++) chk2(c, v[i], tg);
      if (!__any_sync(~0u, c & TAG)) break;
      if (it > POLL_LIMIT) FAIL(2000);
    }
    bar_sync(1 + wg, 128);
#pragma unroll
    for (int i = 0; i < 4; i++) sts16(t16 + (MEM + wg * 6144) + i * 2048, v[i]);
    if (!PRE) landed(gv.prefetch(lds4(wsa(t16))) & zero);
    bar_sync(1 + wg, 128);
  }
}

constexpr int A_WS = 0;
constexpr int A_X = 65536;
constexpr int A_H1 = A_X + 32768;
constexpr int A_MEM = A_X + 98304;
constexpr int A_QX = A_MEM + 16384, A_KX = A_QX + EX_K, A_QM = A_QX + EX_CTA;
constexpr int A_KM = A_QM + 2048;
constexpr int A_SB = A_KM + 2048;
constexpr int A_BARS = A_X + 131072;
constexpr int A_TRC = A_BARS + 256;
constexpr int A_TAB = A_BARS + 1024;
constexpr int A_PQ = A_TAB + 16384;
constexpr int A_SMEM = A_PQ + 8192;
constexpr int B_RES = 64, B_PAIR = 72, B_H0 = 80, B_H1 = 88  , B_M = 104, B_XE = 112, B_EXD = 120, B_HO = 0  , B_T = 128  , B_NEAR = 160, B_EP = 168, B_TK = 176, B_CHK = 184;

template <int NP> struct GemvQK {
  float a[4], b[4], a2[4], b2[4];
  uint4 m[16];
  uint32_t pp[4][16], ws;
  static __device__ __forceinline__ constexpr int blk(int n) {
    return NP == 2 ? (n < 2 ? 12 + n : n == P14 ? 14 : n == P15 ? 15 : n - 2 - (n > P14) - (n > P15)) : (n < 3 ? 12 + n : n == 10 ? 15 : n - 3 - (n > 10));
  }
  static __device__ __forceinline__ constexpr int lm(int n) { return NP == 3 && n < 1 ? n + 3 : NP == 3 && n < 2 ? n + 4 : n + 1 + GLA > 16 ? 16 : n + 1 + GLA; }
  static __device__ __forceinline__ constexpr int lw(int n) {
    return NP == 2 ? (n >= L14 && n < L14 + 4 ? 8 + n - L14 : n >= L15 && n < L15 + 4 ? 12 + n - L15 : 0)
                   : (n >= 3 && n <= 8 && n != 5 && n != 7 ? 9 + n - (n > 5) - (n > 7) : 0);
  }
  template <int J0 = 0, int J1 = NP * 4> __device__ __forceinline__ uint32_t prefetch(uint32_t a) {
    ws = a;
    uint32_t y = ~0u;
#pragma unroll
    for (int j = J0; j < J1; j++) { ldw(pp[j >> 2] + (j & 3) * 4, ws + (j >> 1) * 2048 + (j & 1) * 16384); y &= pp[j >> 2][(j & 3) * 4]; }
    return y;
  }
  template <int N, typename F> __device__ __forceinline__ void run(const uint32_t* w, uint32_t mb, F hook) {
    if constexpr (N < 16) {
      if (N == 0) {
#pragma unroll
        for (int n = 0; n < lm(-1); n++) m[n] = lds16v(mb + blk(n) * 512);
      }
      constexpr int bi = blk(N), o2 = bi >= 12 ? 8 : 4, j = lw(N);
      const uint32_t* pa = bi >= 12 ? pp[bi >= 12 ? bi - 12 : 0] : w + bi * 8;
      const uint32_t* pb = bi >= 12 ? pa + 4 : pa + 96;
      if (N == 0) { MMA_XZ(a, pa, m[N].x, m[N].y); MMA_XZ(b, pb, m[N].x, m[N].y); MMA_XZ(a2, pa + o2, m[N].z, m[N].w); MMA_XZ(b2, pb + o2, m[N].z, m[N].w); }
      else { MMA_X(a, pa, m[N].x, m[N].y); MMA_X(b, pb, m[N].x, m[N].y); MMA_X(a2, pa + o2, m[N].z, m[N].w); MMA_X(b2, pb + o2, m[N].z, m[N].w); }
#pragma unroll
      for (int n = lm(N - 1); n < lm(N); n++) m[n] = lds16v(mb + blk(n) * 512);
      if (j) ldw(pp[j >> 2] + (j & 3) * 4, ws + (j >> 1) * 2048 + (j & 1) * 16384);
      hook(IntC<N>());
      run<N + 1>(w, mb, hook);
    }
  }
  __device__ __forceinline__ void store(uint32_t ad) {
    stsm4t(ad, pack_bf16(a[0] + a2[0], a[1] + a2[1]), pack_bf16(a[2] + a2[2], a[3] + a2[3]), pack_bf16(b[0] + b2[0], b[1] + b2[1]), pack_bf16(b[2] + b2[2], b[3] + b2[3]));
  }
};

#define TKA (bars + B_TK)
__device__ __forceinline__ void qk_body(const CUtensorMap& tmWq, const CUtensorMap& tmWk, const CUtensorMap& tmX,
                                        char* __restrict__ G, const Pace d, int zero, int block, const int CS) {
  extern __shared__ __align__(1024) uint8_t smem_raw[];
  const uint32_t sb = smem_u32(smem_raw);
  if ((sb & 0x3FFFF) != SB0) __trap();
  asm volatile("griddepcontrol.launch_dependents;" ::: "memory");
  const int tid = threadIdx.x, t7 = tid & 127, lane = tid & 31;
  const int warp = UNI(tid >> 5), wg = warp >> 2, w4 = warp & 3;
  const uint32_t wofs = UNI((tid >> 5) * -512);
  const int cta = UNI(block), r = cta & 1, head = cta >> 1, fcol = cta * 64, rank = cta & (CS - 1);
  const uint32_t bars = sb + A_BARS;
  const uint32_t trc = UNI(sb + A_TRC + (tid >> 5) * 64); (void)trc;
  if (tid == 0) {
    STAMP(CS > 2 ? 8 : 11);
    for (int i = 0; i < 32; i++) if ((i & 24) != 16) mbar_init(bars + i * 8, i * 8 == B_XE ? CS : 1);
    asm volatile("fence.mbarrier_init.release.cluster;" ::: "memory");
    sts8f(bars + B_NEAR, __uint_as_float(~0u), __uint_as_float(~0u));
  }
  const uint32_t gu = wpage(L_U + (cta >> 2)) + (cta & 3) * 1024;
  if (tid < 128) *reinterpret_cast<uint4*>(G + ((gu + (tid & 63) * 16) ^ ((tid & 64) << 6))) = make_uint4(0, 0, 0, 0);
  probe_init(G, cta * 8);
  if (tid < 4) *reinterpret_cast<uint32_t*>(G + (wpage(L_FLAG) ^ ((tid & 1) << 12)) + (tid >> 1) * 512 + head * 16 + r * 4) = 30;
  __syncthreads();
  const uint32_t stg = sb + A_X + wg * 65536;
  const uint32_t sbar = bars + wg * 32;
  const int lk = (lane & 7) + ((lane >> 4) << 3);
  const uint32_t wt_off = lk * 128 + (((((tid >> 4) & 6) + ((lane >> 3) & 1)) ^ (lk & 7)) << 4);
  const int g = lane >> 2, c = lane & 3;
  if (t7 == 0) {
    for (int i = 0; i < 4; i++) {
      mbar_expect_tx(sbar + i * 8, 16384);
      tma2d_ef(stg + i * 16384, i < 3 ? &tmWk : &tmWq, fcol, wg * 512 + (i % 3) * 128, sbar + i * 8);
    }
    if (WPF) for (int i = 1; i < 3; i++) tma2d_pf(&tmWq, fcol, wg * 512 + i * 128);
    if (wg == 0) {
      mbar_expect_tx(bars + B_RES, 65536);
      for (int i = 0; i < 4; i++) tma2d_ef(sb + A_WS + i * 16384, (i & 1) ? &tmWq : &tmWk, fcol, (i >> 1) * 512 + 384, bars + B_RES);
    }
  }
  if (tid == 64) start_arrive(bars + B_EP);
  __syncwarp();
  uint32_t w[192];
  const uint32_t t16_ = OPQ(sb + tid * 16);
#pragma unroll
  for (int i = 0; i < 6; i++) {
    mbar_wait(sbar + (i & 3) * 8, i >> 2);
#pragma unroll
    for (int j = 0; j < 8; j++) ldw(w + (i * 8 + j) * 4, stg + (i & 3) * 16384 + j * 2048 + wt_off);
    if (i == 1) {
      bar_sync(1 + wg, 128);
      if (t7 == 0)
        for (int i2 = 4; i2 < 6; i2++) {
          mbar_expect_tx(sbar + (i2 & 3) * 8, 16384);
          tma2d_ef(stg + (i2 & 3) * 16384, &tmWq, fcol, wg * 512 + (i2 - 3) * 128, sbar + (i2 & 3) * 8);
        }
      if (lane == 0) probe_near(G, cta * 8 + (tid >> 5), bars + B_NEAR);
      __syncwarp();
    }
  }
  mbar_wait(bars + B_RES, 0);
  if (tid == 0) STAMP(21);
  __syncwarp();
  cluster_sync();
  if (tid == 0) STAMP(CS > 2 ? 9 : 12);
  const uint32_t near = pick_near(CS, A_BARS + B_NEAR);
  if (tid == 0) st_relaxed4(&g_rings.side[cta], lds4(bars + B_EP) + (near >> 12));
  auto fetch_x = [&](uint32_t buf, uint32_t bar, int n, int h) __attribute__((always_inline)) {
    if (CS == 8) issue_x(&tmX, sb + buf + rank * 4096, bars + bar, n, h * 8 + rank, 255);
    else issue_x(&tmX, sb + buf + rank * 16384, bars + bar, n, h * 8 + rank * 4, 3);
  };
  if (warp == 7) {
    expect(bars + B_H0, 32768); expect(bars + B_H1, 32768); expect(bars + B_H1 + 8, 32768);
    fetch_x(A_H1, B_H1, 0, 1); fetch_x(A_X, B_H0, 0, 0); fetch_x(A_H1 + 32768, B_H1 + 8, 1, 1);
    expect(bars + B_PAIR, 1536);
    expect(bars + B_M, 16384);
  }
  const uint32_t rdelta = UNI(mapa(sb, rank ^ 1) - sb);
  {
    const int w4 = (tid >> 5) & 3, wg = tid >> 7;
    const int ch = 2 * w4 + ((lane >> 3) & 1);
    const uint32_t qst = sb + (lane & 7) * 16 + ((lane >> 4) ? A_QM + ch * 256 + wg * 128 : A_KM + wg * 1024 + ch * 128);
    const uint32_t fst = sb + (lane & 7) * 16 + (wg ? A_QX + w4 * 1024 + (lane >> 3) * 128 : A_KX + ch * 640 + (lane >> 4) * 128);
    const uint32_t kba = sb + (wg && w4 < 2 ? A_KM + w4 * 1024 + lane * 16 : (lane & 7) * 16 + A_KX + (lane >> 3) * 640 + (wg ? 4 : w4) * 128);
    const char* vmp = G + ((wpage(L_VM + head) ^ near) + r * 2048 + t7 * 8);
    const char* up = G + ((gu ^ near ^ 4096) + (w4 >> 1) * 512 + g * 64 + (w4 & 1) * 32 + c * 8);
    const char* vxp = G + ((wpage(cta) ^ near) + VX0 + w4 * 1024 + lane * 16);
    sts16(t16_ + A_TAB, make_uint4(sb + A_MEM + tid * 32 + ((lane >> 2) & 3) * 8, qst, kba, sb + A_SB + lane * 16 + (w4 & 1) * 8 + min(tid >> 6, 2) * 512));
    sts16(t16_ + A_TAB + 4096, make_uint4(plo(vmp), phi(vmp), plo(vxp), phi(vxp)));
    sts16(t16_ + A_TAB + 8192, make_uint4(sb + rdelta + A_SB + 1536 + tid * 8, bars + B_PAIR + rdelta, fst, sb + A_WS + wg * 32768 + wt_off));
    sts16(t16_ + A_TAB + 12288, make_uint4(plo(up), phi(up), plo(up) ^ 4096, phi(up)));
    if (tid == 0) { const uint32_t t = gtime() * 9; sts16(bars + B_T, make_uint4(t, t, d.u0, d.m0)); sts4f(bars + B_T + 16, __uint_as_float(t - 1)); sts4f(bars + B_CHK, 0.f); }
  }
  __syncthreads();
  auto fetch_mem = [&](uint32_t slot, auto wait) __attribute__((always_inline)) {
    if (CS == 8) { wait(); fetch_mem_mc<8>(sb + A_MEM, G, near + slot, rank, bars + B_M); }
    else {
      wait();
#pragma unroll
      for (int p = 0; p < 4; p++) bulk(sb + A_MEM + p * 4096, G + (near + slot) + wpage(L_MEM + p), 4096, bars + B_M);
    }
  };
  const uint32_t hob = UNI(sb + A_BARS + 192 + ((tid >> 2) & 24));
  auto proj = [&](int s, auto& gv, auto wg_c, auto gate, auto mid, auto between, auto mid2, auto mid3) __attribute__((always_inline)) {
    constexpr int wg = decltype(wg_c)::value, XB = wg ? A_H1 : A_X;
    uint32_t z = wg ? ((s + 1) & 1) * 2048 : s & wofs & zero;
    float d[16];
    uint32_t f[8];
    auto pass = [&](auto m_c, auto first_c) __attribute__((always_inline)) {
      constexpr int m = decltype(m_c)::value;
      constexpr bool first = decltype(first_c)::value;
      if (first) {
        const uint32_t ws = lds4v(t16_ + A_TAB + 8204);
        gate([&](uint32_t z) __attribute__((always_inline)) { gv.template prefetch<0, 4>(ws | z); });
      }
      WG_FENCE();
#pragma unroll
      for (int k = 0; k < XQ; k++) {
        if (k == 0) wg_rs32<0>(d, w + m * 96, cdesc(z, XB)); else wg_rs32<1>(d, w + m * 96 + 4 * k, cdesc(wg || k < ZN ? z : 0, XB + xk(k)));
      }
#pragma unroll
      for (int j = 2; j < XS; j++) wg_ss32(d, cdesc(0, A_WS + wg * 32768 + m * 16384 + j * 2048), cdesc(wg ? z : 0, XB + xk(24 + j)));
#pragma unroll
      for (int j = 0; j < 2; j++) wg_rs32<1>(d, gv.pp[0] + j * 8 + m * 4, cdesc(wg ? z : 0, XB + xk(24 + j)));
      WG_COMMIT();
    };
    pass(IntC<1 - wg>(), BoolC<true>());
    TR(8);
    mid();
    z = wg ? UNI(z | zero) : 0;
    WG_WAIT(0);
    TR(9);
    acc_fence16(d);
    sts16(t16_ + A_PQ, make_uint4(pack_bf16(d[0], d[1]), pack_bf16(d[2], d[3]), pack_bf16(d[4], d[5]), pack_bf16(d[6], d[7])));
    sts16(t16_ + A_PQ + 4096, make_uint4(pack_bf16(d[8], d[9]), pack_bf16(d[10], d[11]), pack_bf16(d[12], d[13]), pack_bf16(d[14], d[15])));
    __syncwarp();
    asm volatile(ELECT "mbarrier.arrive.shared::cta.b64 _, [%0];}" ::"r"(hob + wg * 32) : "memory");
    between();
    pass(IntC<wg>(), BoolC<false>());
    mid2();
    wait_ft(hob + 32 - wg * 32, (s + 1) & 1);
    const uint4 p0 = lds16v(t16_ + A_PQ + 2048 - wg * 4096), p1 = lds16v(t16_ + A_PQ + 6144 - wg * 4096);
    const uint2 tc = lds8v(t16_ + A_TAB + 8200);
    if (ATT) wait_ft(bars + B_EXD, s & 1);
    mid3();
    TR(10);
    WG_WAIT(0);
    TR(11);
    acc_fence16(d);
    const uint32_t p[8] = {p0.x, p0.y, p0.z, p0.w, p1.x, p1.y, p1.z, p1.w};
#pragma unroll
    for (int i = 0; i < 8; i++) f[i] = pack_bf16(d[2 * i] + __uint_as_float(p[i] << 16), d[2 * i + 1] + __uint_as_float(p[i] & 0xFFFF0000u));
    stsm4t(tc.x, f[0], f[1], f[2], f[3]); stsm4t(tc.x + (wg ? 512 : 256), f[4], f[5], f[6], f[7]);
    gv.template prefetch<4>(tc.y);
  };
  auto fetch_h1 = [&](int s, int w4) __attribute__((always_inline)) {
    if (w4 == 1 && s + 2 < NSEG) {
      expect(bars + B_H1 + (s & 1) * 8, 32768);
      fetch_x(A_H1 + (s & 1) * 32768, B_H1 + (s & 1) * 8, s + 2, 1);
    }
  };
  auto send_qk = [&](int s) __attribute__((always_inline)) {
    asm volatile(ELECT "cp.async.bulk.global.shared::cta.bulk_group [%0], [%1], %2;}"
                 ::"l"(reinterpret_cast<char*>(g_rings.ex[s & 3]) + cta * EX_CTA), "r"(sb + A_QX), "r"(EX_CTA) : "memory");
    asm volatile("cp.async.bulk.commit_group;" ::: "memory");
  };
  auto sent_qk = [&]() __attribute__((always_inline)) {
    asm volatile("cp.async.bulk.wait_group 0;" ::: "memory");
    __syncwarp();
    asm volatile(ELECT "mbarrier.arrive.shared::cta.b64 _, [%0];}" ::"r"(bars + B_EXD) : "memory");
  };
  auto sum_km = [&]() __attribute__((always_inline)) {
    BASES();
    const uint32_t ka = lds4(t16 + A_TAB + 8);
    uint32_t kb[16];
#pragma unroll
    for (int i = 0; i < 4; i++) ldm(kb + 4 * i, l16 + A_KM + i * 512);
#pragma unroll
    for (int i = 0; i < 8; i++) asm("add.rn.bf16x2 %0, %0, %1;" : "+r"(kb[i]) : "r"(kb[8 + i]));
    stsm4(ka, kb[0], kb[1], kb[2], kb[3]); stsm4(ka + 2560, kb[4], kb[5], kb[6], kb[7]);
  };
  auto chores = [&](int s, int w4) __attribute__((always_inline)) {
    if (w4 == 1 || w4 == 2) {
      spin_coarse(lds4(bars + B_T + 4 + (s & 1) * 16) + d.c);
    }
    if (ATT && w4 == 2 && !(EXPT & 32)) send_qk(s);
    fetch_h1(s, w4);
  };
  if (tid == 0) STAMP(22);
  __syncwarp();
  mbar_wait(bars + B_H1, 0);
  if (tid == 0) STAMP(23);
  __syncwarp();
  auto gemv = [&](auto& gv, int s, auto wg_c, uint4& ta, uint2& tr, auto late) __attribute__((always_inline)) {
    constexpr int wg = decltype(wg_c)::value;
    BASES();
    TR(14);
    wait_ft(bars + B_M, s & 1);
    TR(0);
    uint32_t h0, h1;
    gv.template run<0>(w, l16 + A_MEM + wg * 8192, [&](auto nc) __attribute__((always_inline)) {
      constexpr int N = decltype(nc)::value;
      if (N == CK0) ta = lds16v(t16 + A_TAB);
      if (N == CK0 + 1) { h0 = lds4v(ta.x); h1 = lds4v(ta.x + 8192); }
      if (N == CK0 + 2) {
        const uint32_t tg = (s & 1) << 16;
        asm volatile("{.reg .pred p; setp.ne.u32 p, %1, 0; @p st.shared.u32 [%0], %2;}" ::"r"(bars + B_CHK), "r"(((h0 ^ tg) | (h1 ^ tg)) & TAG), "r"(s) : "memory");
      }
      if (N == LN) {
        tr = lds8v(t16 + A_TAB + 8192);
        late();
        if (PINA) HERE(ta.y);
      }
    });
  };
  auto scores = [&](const uint4& ta, const uint2& tr, const uint32_t* kb) __attribute__((always_inline)) {
    BASES();
    float sp[4][4];
    uint32_t a[16];
    const uint32_t chk = lds4v(bars + B_CHK + (t16 & zero));
#pragma unroll
    for (int i = 0; i < 4; i++) ldm(a + 4 * i, l16 + A_QM + i * 512);
#pragma unroll
    for (int i = 0; i < 4; i++) MMA_XZ(sp[i], a + 4 * i, kb[2 * i], kb[2 * i + 1]);
    const float x = (((sp[0][0] + sp[0][2]) + (sp[1][0] + sp[1][2])) + (sp[2][0] + sp[2][2])) + (sp[3][0] + sp[3][2]);
    const float y = (((sp[0][1] + sp[0][3]) + (sp[1][1] + sp[1][3])) + (sp[2][1] + sp[2][3])) + (sp[3][1] + sp[3][3]);
    st_async8(chk ? t16 + A_PQ : tr.x, x, y, chk ? bars : tr.y);
    sts8f(ta.w, x, y);
    return chk;
  };
  auto repair = [&](auto& gv, int s) __attribute__((always_inline)) {
    CNT(0);
    BASES();
    uint4 v[4];
    const char* src = G + (near + ((t16 - SB0) & 0xFF0));
    for (int it = 0;; it++) {
      uint32_t c = 0;
#pragma unroll
      for (int i = 0; i < 4; i++) v[i] = ld_tagged16(src + wpage(L_MEM + i));
#pragma unroll
      for (int i = 0; i < 4; i++) chk2(c, v[i], (s & 1) << 16);
      if (!__any_sync(~0u, c & TAG)) break;
      if (it > POLL_LIMIT) FAIL(2000);
    }
#pragma unroll
    for (int i = 0; i < 4; i++) sts16(t16 + A_MEM + i * 4096, v[i]);
    gv.prefetch(lds4(t16 + A_TAB + 8204));
    bar_sync(14, 256);
    sts4f(bars + B_CHK, 0.f);
    bar_sync(14, 256);
  };
  if (wg == 0) {
    bar_arrive(3, 256);
#pragma unroll 1
    for (int s = UNI(zero - 1);;) {
      GemvQK<2> gv;
      const int s1 = UNI(s + 1);
      proj(s, gv, IntC<0>(), [&](auto pre) __attribute__((always_inline)) { pre(0); wait_ft(bars + B_H0, (s + 1) & 1); TR(5); },
           [&]() __attribute__((always_inline)) {
        if (w4 == 2 && s >= 0) {
          const uint4 pl = lds16(bars + B_T + (s & 1) * 16);
          spin_coarse(pl.y + LOOKD * 5);
          const char* fl = flag_ptr(G, near, t16_, s);
          sts16(bars + B_T + (~s & 1) * 16, next_plan(pl, last_stores(ld_relaxed16(fl), fl, s), s, d));
          bar_arrive(6, 64);
        }
      }, []() {}, []() {}, []() {});
      if (s >= 0) TRD(cta);
      s = s1;
      uint4 tb, v0, v1, tu4;
      float4 p0, p1, p2;
      uint2 va, vb;
      const char *vxp, *vmp;
#pragma unroll 1
      for (;;) {
        uint4 ta;
        uint2 tr;
        uint32_t kb[8];
        gemv(gv, s, IntC<0>(), ta, tr, [&]() __attribute__((always_inline)) {
          ldm(kb, ta.z); ldm(kb + 4, ta.z + 2560);
        });
        gv.store(ta.y);
        tb = lds16v(t16_ + A_TAB + 4096);
        TR(1);
        bar_sync(7, 256);
        const uint32_t chk = scores(ta, tr, kb);
        TR(3);
        bar_sync(9, 192);
        BASES();
        p0 = lds16fv(l16 + A_SB); p1 = lds16fv(l16 + A_SB + 512); p2 = lds16fv(l16 + A_SB + 1024);
        tu4 = lds16v(t16 + A_TAB + 12288);
        vxp = ptr64(tb.z + (s & 1) * 16384, tb.w);
        v0 = ld_tagged16(vxp); v1 = ld_tagged16(vxp + 512);
        vmp = ptr64(tb.x, tb.y);
        va = ld_tagged8(vmp); vb = ld_tagged8(vmp + 1024);
        if (__builtin_expect(!__any_sync(~0u, chk), 1)) break;
        repair(gv, s);
      }
      BASES();
      const uint32_t l8 = ((l16 >> 1) + ((sb >> 1) + A_SB + 1536)) | (tu4.x & zero);
      p0.x *= SCL; p0.y *= SCL; p0.z *= SCL; p0.w *= SCL; p1.x *= SCL; p1.y *= SCL; p1.z *= SCL; p1.w *= SCL; p2.x = (p2.x + p2.z) * SCL; p2.y = (p2.y + p2.w) * SCL;
      wait_ft(bars + B_PAIR, s & 1);
      TR(4);
      float sc[10];
      {
        const float2 q4 = lds8f(l8 + 1024), q5 = lds8f(l8 + 1280), q0 = lds8f(l8), q1 = lds8f(l8 + 256), q2 = lds8f(l8 + 512), q3 = lds8f(l8 + 768);
        sc[0] = fmaf(q0.x, SCL, p0.x); sc[1] = fmaf(q0.y, SCL, p0.y); sc[2] = fmaf(q1.x, SCL, p0.z); sc[3] = fmaf(q1.y, SCL, p0.w);
        sc[4] = fmaf(q2.x, SCL, p1.x); sc[5] = fmaf(q2.y, SCL, p1.y); sc[6] = fmaf(q3.x, SCL, p1.z); sc[7] = fmaf(q3.y, SCL, p1.w);
        sc[8] = fmaf(q5.x, SCL, fmaf(q4.x, SCL, p2.x)); sc[9] = fmaf(q5.y, SCL, fmaf(q4.y, SCL, p2.y));
      }
      exp10v(sc);
      uint32_t p[5];
#pragma unroll
      for (int i = 0; i < 5; i++) p[i] = pack_bf16(sc[2 * i], sc[2 * i + 1]);
      const uint32_t tu = (~s & 1) << 16, tx = (~s & 2) << 15;
      auto pv = [&](bool ok) __attribute__((always_inline)) {
        float o0[4], o1[4], os[4], m0[4], m1[4];
        const uint32_t j0 = junk(), j1 = junk(), j2 = junk(), j3 = junk(), j4 = junk();
        mma_z(os, p[0], j0, p[1], j1, ONE2, ONE2); mma_z(o0, p[0], j0, p[1], j1, v0.x, v0.y); mma_z(o1, p[0], j0, p[1], j1, v1.x, v1.y);
        mma16816(os, p[2], j2, p[3], j3, ONE2, ONE2); mma16816(o0, p[2], j2, p[3], j3, v0.z, v0.w); mma16816(o1, p[2], j2, p[3], j3, v1.z, v1.w);
        mma1688(os, p[4], j4, ONE2);
        mma1688z(m0, p[4], j4, vb.x); mma1688z(m1, p[4], j4, vb.y);
        mma1688(o0, p[4], j4, va.x); mma1688(o1, p[4], j4, va.y);
        const float inv = rcp_fast(os[0]);
        const uint32_t u0 = pack_tag((o0[0] + m0[0]) * inv, (o0[1] + m0[1]) * inv, tu), u1 = pack_bf16((o1[0] + m1[0]) * inv, (o1[1] + m1[1]) * inv);
        st_tagged8_if(ptr64(tu4.x, tu4.y), u0, u1, ok);
        st_tagged8_if(ptr64(tu4.z, tu4.w), u0, u1, ok);
      };
      if (EXPT & 2) { v0.x = tx; v1.x = tx; }
      const bool bad = __any_sync(~0u, ((va.x ^ tu) | (vb.x ^ tu) | (v0.x ^ tx) | (v1.x ^ tx)) & TAG);
      pv(!bad);
      if (__builtin_expect(bad, 0)) {
        CNT(1);
        int it = 0;
        do {
          v0 = ld_tagged16(vxp); v1 = ld_tagged16(vxp + 512);
          va = ld_tagged8(vmp); vb = ld_tagged8(vmp + 1024);
          if (EXPT & 2) { v0.x = tx; v1.x = tx; }
          if (++it > POLL_LIMIT) FAIL(3000 + s);
        } while (__any_sync(~0u, ((va.x ^ tu) | (vb.x ^ tu) | (v0.x ^ tx) | (v1.x ^ tx)) & TAG));
        pv(true);
      }
      if (s == NSEG - 1) break;
      bar_arrive(3, 256);
      TR(7);
      bar_sync(1, 128);
      if (w4 == 1) {
        const uint32_t c0 = clk32();
        st_relaxed4_if(ptr64(plo(G) + ((wpage(L_FLAG) ^ ((t16 & 16) << 8)) + ((s & 1) * 512 + head * 16 + r * 4)), phi(G)),
                       ((c0 * 5 + time_offset(t16 & zero)) & ~31u) | (s & 31), (t16 & 0x1E0) == 0);
      }
    }
  } else {
#pragma unroll 1
    for (int s = UNI(zero - 1);;) {
      GemvQK<NPRE> gv;
      const int s1 = UNI(s + 1), ro = s < 0 ? w4 + 4 : w4;
      auto pace = [&]() __attribute__((always_inline)) {
        if (ro == 3) {
          bar_sync(6, 64);
          const uint32_t tm = lds4(bars + B_T + (~s & 1) * 16), tk = approach(tm, t16_ & zero);
          TRK(tk);
          fetch_mem(0, [&]() __attribute__((always_inline)) { spin_until(tm, tk); TR(12); });
        }
        if (ro == 7) {
          start_wait(bars + B_EP);
          fetch_mem(16384, []() {});
        }
      };
      proj(s, gv, IntC<1>(), [&](auto pre) __attribute__((always_inline)) {
        if (ro == 3) expect(bars + B_M, 16384);
        if (ro == 0) wait_ft(bars + B_H1 + ((s + 1) & 1) * 8, ((s + 1) >> 1) & 1);
        if (ro == 1) { wait_ft(bars + B_XE, s & 1); if (H0POS == 1) fetch_x(A_X, B_H0, s + 1, 0); }
        wait_ft(bars + B_PAIR, s & 1);
        const uint32_t c0 = clk32();
        if (ro == 1) { if (H0POS == 0) fetch_x(A_X, B_H0, s + 1, 0); expect(bars + B_PAIR, 1536); }
        spin_until((c0 + QUIET) * 5, 0);
        pre(0);
        if (ATT && ro == 2) sum_km();
        TR(6);
        bar_sync(3, 256);
        TR(7);
      }, [&]() __attribute__((always_inline)) {
      }, [&]() __attribute__((always_inline)) {
        if (ATT && ro == 2) { asm volatile("fence.proxy.async.shared::cta;" ::: "memory"); __syncwarp(); }
        if (CHPOS == 0) chores(s, ro);
      }, [&]() __attribute__((always_inline)) {
        if (CHPOS == 1) chores(s, ro);
        if (ATT && ro == 2) sent_qk();
        if (PACE == 2) pace();
      }, [&]() __attribute__((always_inline)) { if (PACE == 3) pace(); });
      if (KEEP && ro == 0) {
#pragma unroll 1
        for (int it = 0; it < 4096; it++) {
          const uint32_t t0 = lds4v(bars + B_T + (s & 1) * 16), t1 = lds4v(bars + B_T + (~s & 1) * 16);
          if (__any_sync(~0u, t1 - t0 < (1u << 31) && (int)(gtime() * 9 - t1) > 0)) break;
          float e[4];
          mma1688z(e, t0, t0, t0);
          sts4f(bars + B_EP + 4, e[0]);
        }
      }
      if (s >= 0) TRD(cta);
      s = s1;
#pragma unroll 1
      for (;;) {
        uint4 ta;
        uint2 tr;
        gemv(gv, s, IntC<1>(), ta, tr, []() {});
        gv.store(ta.y);
        TR(1);
        bar_sync(7, 256);
        uint32_t chk;
        if (__builtin_expect(w4 < 2, 1)) {
          uint32_t kb[8];
          ldm(kb, ta.z); ldm(kb + 4, ta.z + 512);
          chk = scores(ta, tr, kb);
          bar_arrive(9, 192);
        } else {
          chk = lds4v(bars + B_CHK);
          if (w4 == 3 && s < NSEG - 1 && !__any_sync(~0u, chk)) {
            expect(bars + B_H0, 32768);
            arrive_all(CS, t16_, A_BARS + B_XE);
            if (H0POS == 2) { wait_ft(bars + B_XE, s & 1); fetch_x(A_X, B_H0, s + 1, 0); }
          }
        }
        TR(3);
        if (__builtin_expect(!__any_sync(~0u, chk), 1)) break;
        repair(gv, s);
      }
      if (s == NSEG - 1) break;
    }
  }
  if (warp == 6) {
    sum_km();
    asm volatile("fence.proxy.async.shared::cta;" ::: "memory");
    __syncwarp();
    send_qk(NSEG - 1);
    sent_qk();
    if (lane < 2) st_relaxed4(G + (wpage(L_FLAG) ^ (lane << 12)) + 512 + head * 16 + r * 4, (NSEG - 1) & 31);
  }
  mbar_wait(bars + B_PAIR, (NSEG - 1) & 1);
  __syncwarp();
  cluster_sync();
  if (tid == 0) STAMP(CS > 2 ? 10 : 13);
  if (blockIdx.x == 0) asm volatile("griddepcontrol.wait;" ::: "memory");
}
__global__ void __launch_bounds__(256, 1)
qk_kernel(const __grid_constant__ CUtensorMap tmWq, const __grid_constant__ CUtensorMap tmWk, const __grid_constant__ CUtensorMap tmX,
          char* __restrict__ G, const Pace d, int zero, int cta0, int cs) {
  qk_body(tmWq, tmWk, tmX, G, d, zero, blockIdx.x + cta0, cs);
}

constexpr int V_WV = 0;
constexpr int V_WO = 32768;
constexpr int V_X = 65536;
constexpr int V_MEM = V_X + 65536;
constexpr int V_U = V_MEM + 16384;
constexpr int V_EX = V_U + 32768;
constexpr int V_VT = V_EX + EX_BYTES;
constexpr int V_OUT = V_VT + 4 * 6144;
constexpr int V_TAB = V_OUT + 4096;
constexpr int V_BARS = V_TAB + 2048;
constexpr int V_RB = V_BARS + 512;
constexpr int V_TB3 = V_RB + 512;
constexpr int V_TRC = V_TB3 + 512;
constexpr int V_ONE = V_TRC + 512;
constexpr int V_SMEM = V_ONE + 384;
constexpr int C_XF = 80  , C_XE = 96  , C_M = 112, C_EXR = 120, C_U = 128  , C_EX = 144, C_EXE = 152, C_T = 160  , C_NEAR = 176, C_TK = 192;
#define VPIN 0
#define VLB 3
#define PF1 1
#define PF0 3
#define OLA 4
#define UPOS 1
#define OPOS 1
#define VDEP 1
#define SSF 24
#define B6 1
#define PVG 1
#define VC0 3
#define VC1 7
#define VC2 11
#define EXPOS 1
#define VPRE 4
#define VLA 3
#define UW 3
#define RDLY 0
#define VB 0
#define XV 32
#define X0POS 2

#define ACC8(d, o) "+f"(d[o]), "+f"(d[o + 1]), "+f"(d[o + 2]), "+f"(d[o + 3]), "+f"(d[o + 4]), "+f"(d[o + 5]), "+f"(d[o + 6]), "+f"(d[o + 7])
#define OUT8(d, o) "=f"(d[o]), "=f"(d[o + 1]), "=f"(d[o + 2]), "=f"(d[o + 3]), "=f"(d[o + 4]), "=f"(d[o + 5]), "=f"(d[o + 6]), "=f"(d[o + 7])
#define R20 "{%0,%1,%2,%3,%4,%5,%6,%7,%8,%9,%10,%11,%12,%13,%14,%15,%16,%17,%18,%19}"
#define R32 "{%0,%1,%2,%3,%4,%5,%6,%7,%8,%9,%10,%11,%12,%13,%14,%15,%16,%17,%18,%19,%20,%21,%22,%23,%24,%25,%26,%27,%28,%29,%30,%31}"
template <int ACC> __device__ __forceinline__ void wg_ss40(float* d, uint64_t da, uint64_t db) {
  if (ACC) asm volatile("wgmma.mma_async.sync.aligned.m64n40k16.f32.bf16.bf16 " R20 ", %20, %21, 1, 1, 1, 0, 0;"
                        : ACC8(d, 0), ACC8(d, 8), "+f"(d[16]), "+f"(d[17]), "+f"(d[18]), "+f"(d[19]) : "l"(da), "l"(db));
  else asm volatile("wgmma.mma_async.sync.aligned.m64n40k16.f32.bf16.bf16 " R20 ", %20, %21, 0, 1, 1, 0, 0;"
                    : OUT8(d, 0), OUT8(d, 8), "=f"(d[16]), "=f"(d[17]), "=f"(d[18]), "=f"(d[19]) : "l"(da), "l"(db));
}
template <int ACC> __device__ __forceinline__ void wg_rs64(float* d, uint32_t a0, uint32_t a1, uint32_t a2, uint32_t a3, uint64_t db) {
  if (ACC) asm volatile("wgmma.mma_async.sync.aligned.m64n64k16.f32.bf16.bf16 " R32 ", {%32,%33,%34,%35}, %36, 1, 1, 1, 0;"
                        : ACC8(d, 0), ACC8(d, 8), ACC8(d, 16), ACC8(d, 24) : "r"(a0), "r"(a1), "r"(a2), "r"(a3), "l"(db));
  else asm volatile("wgmma.mma_async.sync.aligned.m64n64k16.f32.bf16.bf16 " R32 ", {%32,%33,%34,%35}, %36, 0, 1, 1, 0;"
                    : OUT8(d, 0), OUT8(d, 8), OUT8(d, 16), OUT8(d, 24) : "r"(a0), "r"(a1), "r"(a2), "r"(a3), "l"(db));
}

template <int ACC> __device__ __forceinline__ void wg_rs8(float* d, uint32_t a0, uint32_t a1, uint32_t a2, uint32_t a3, uint64_t db) {
  if (ACC) asm volatile("wgmma.mma_async.sync.aligned.m64n8k16.f32.bf16.bf16 {%0,%1,%2,%3}, {%4,%5,%6,%7}, %8, 1, 1, 1, 0;"
                        : "+f"(d[0]), "+f"(d[1]), "+f"(d[2]), "+f"(d[3]) : "r"(a0), "r"(a1), "r"(a2), "r"(a3), "l"(db));
  else asm volatile("wgmma.mma_async.sync.aligned.m64n8k16.f32.bf16.bf16 {%0,%1,%2,%3}, {%4,%5,%6,%7}, %8, 0, 1, 1, 0;"
                    : "=f"(d[0]), "=f"(d[1]), "=f"(d[2]), "=f"(d[3]) : "r"(a0), "r"(a1), "r"(a2), "r"(a3), "l"(db));
}

struct GemvV {
  float a[4], b[4], a2[4], b2[4];
  uint4 m[16];
  uint32_t pp[4][8], z0, c, tg;
  static __device__ __forceinline__ constexpr int blk(int n) { return (n + 12) & 15; }
  static __device__ __forceinline__ constexpr int lm(int n) {
    const int a = n + 1 + VLA + (n < 2 ? 0 : n - 1 > VLB ? VLB : n - 1);
    return a > 16 ? 16 : a;
  }
  __device__ __forceinline__ uint32_t prefetch(uint32_t ws) {
    uint32_t y = ~0u;
#pragma unroll
    for (int j = 0; j < 8; j++) { ldw(pp[j >> 1] + (j & 1) * 4, ws + j * 2048); y &= pp[j >> 1][(j & 1) * 4]; }
    return y;
  }
  __device__ __forceinline__ void first(uint32_t mb) {
#pragma unroll
    for (int n = 0; n < lm(-1); n++) m[n] = lds16v(mb + blk(n) * 512);
  }
  template <int N, int END, typename F> __device__ __forceinline__ void run(const uint32_t* w, uint32_t mb, F hook) {
    if constexpr (N < END) {
      const uint32_t* p = N < 4 ? pp[N & 3] : w + 96 + blk(N) * 8;
      float* d0 = (N & 1) ? a2 : a;
      float* d1 = (N & 1) ? b2 : b;
      if (N < 2) MMA_XZ(d0, p, m[N].x, m[N].y); else MMA_X(d0, p, m[N].x, m[N].y);
      hook(IntC<2 * N>());
      if (VDEP == 2) { c |= m[N].x ^ tg; m[N].z |= c & z0; }
      if (N < 2) MMA_XZ(d1, p + 4, m[N].z, m[N].w); else MMA_X(d1, p + 4, m[N].z, m[N].w);
      if (VDEP < 2) c |= m[N].x ^ tg;
#pragma unroll
      for (int n = lm(N - 1); n < lm(N); n++) m[n] = lds16v((VDEP == 1 ? mb | (c & z0) : mb) + blk(n) * 512);
      hook(IntC<2 * N + 1>());
      run<N + 1, END>(w, mb, hook);
    }
  }
  static constexpr int CV = 31;
};

#undef TKA
#define TKA (bars + C_TK)
template <int CS>
__device__ __forceinline__ void vo_body(const CUtensorMap& tmWv, const CUtensorMap& tmWo, const CUtensorMap& tmX, const CUtensorMap& tmU, const bf16* __restrict__ mem0,
                                        const bf16* __restrict__ xin, char* __restrict__ G, const Pace d, int zero, int block) {
  extern __shared__ __align__(1024) uint8_t smem_raw[];
  const uint32_t sb = smem_u32(smem_raw);
  if ((sb & 0x3FFFF) != SB0) __trap();
  if (block == 0) {
    if (threadIdx.x < 40) { reinterpret_cast<int4*>(g_rings.ctr)[threadIdx.x] = make_int4(-1, -1, -1, -1); __threadfence(); }
    __syncthreads();
  }
  asm volatile("griddepcontrol.launch_dependents;" ::: "memory");
  const int tid = threadIdx.x, t7 = tid & 127, lane = tid & 31;
  const int warp = UNI(tid >> 5), wg = warp >> 2, w4 = warp & 3;
  const uint32_t wofs = UNI((tid >> 5) * -512);
  const int cta = UNI(block), r = cta & 1, head = cta >> 1, fcol = cta * 64, rank = cta & (CS - 1);
  constexpr uint32_t ALL = (1u << CS) - 1;
  const uint32_t bars = sb + V_BARS;
  const uint32_t trc = UNI(sb + V_TRC + (tid >> 5) * 64); (void)trc;
  if (tid == 0) {
    STAMP(0);
    for (int i = 0; i < 20; i++) mbar_init(bars + i * 8, i * 8 == C_XE ? 4 * CS : i * 8 == C_XE + 8 ? 3 * CS : i * 8 == C_EXE ? 8 : 1);
    asm volatile("fence.mbarrier_init.release.cluster;" ::: "memory");
    sts8f(bars + C_NEAR, __uint_as_float(~0u), __uint_as_float(~0u));
  }
  const uint32_t gm = wpage(L_MEM + (head >> 3)) + (head & 7) * 512 + r * 256;
  {
    const uint4 z = make_uint4(0, 0, 0, 0);
    *reinterpret_cast<uint4*>(G + ((wpage(L_VM + head) + r * 2048 + t7 * 16) ^ (wg << 12))) = z;
    if (tid < 4) *reinterpret_cast<uint32_t*>(G + (wpage(L_FLAG) ^ ((tid & 1) << 12)) + (tid >> 1) * 512 + head * 16 + 8 + r * 4) = 0;
    for (int i = 0; i < 4; i++) *reinterpret_cast<uint4*>(G + ((wpage(cta) ^ ((i & 1) << 12)) + VX0 + (i >> 1) * 16384 + tid * 16)) = z;
    probe_init(G, 512 + cta * 8);
    if (tid < 64) {
      const uint32_t* m0 = reinterpret_cast<const uint32_t*>(mem0) + (4 * r + (lane >> 3)) * (DM / 2) + head * 16 + (lane & 1) * 8 + ((lane & 7) >> 1);
      char* p = G + ((gm + lane * 8) ^ (warp << 12));
      *reinterpret_cast<uint2*>(p) = make_uint2(0, 0);
      *reinterpret_cast<uint2*>(p + 16384) = make_uint2(m0[0], m0[4]);
    }
  }
  __syncthreads();
  const uint32_t stg = sb + V_X + wg * 65536;
  const uint32_t sbar = bars + wg * 32;
  const int lk = (lane & 7) + ((lane >> 4) << 3);
  const uint32_t wt_off = lk * 128 + (((((tid >> 4) & 6) + ((lane >> 3) & 1)) ^ (lk & 7)) << 4);
  const int g = lane >> 2, c = lane & 3;
  if (t7 == 0) {
    for (int i = 0; i < 4; i++) {
      mbar_expect_tx(sbar + i * 8, 16384);
      for (int t = 0; t < 2; t++)
        tma2d(stg + i * 16384 + t * 8192, &tmWo, head * 32, r * 2048 + (wg * 4 + i) * 256 + t * 128, sbar + i * 8);
    }
    if (WPF) for (int i = 0; i < 3; i++) tma2d_pf(&tmWv, fcol, wg * 512 + i * 128);
    if (wg == 0) {
      mbar_expect_tx(bars + B_RES, 32768);
      for (int i = 0; i < 2; i++) tma2d_ef(sb + V_WV + i * 16384, &tmWv, fcol, i * 512 + 384, bars + B_RES);
    }
  }
  if (tid == 32 && cta < XP) asm volatile("cp.async.bulk.prefetch.L2.global [%0], 32768;" ::"l"(xin + (size_t)cta * 16384) : "memory");
  if (tid == 64) start_arrive(bars + C_NEAR + 8);
  __syncwarp();
  uint32_t w[192];
  const uint32_t t16_ = OPQ(sb + tid * 16);
  __syncwarp();
  mbar_wait(sbar + w4 * 8, 0);
  __syncwarp();
  {
    const int rr = lane & 7, mi = lane >> 3, cc = rr >> 1;
    const uint32_t a = stg + ((tid >> 5) & 3) * 16384 + ((cc >> 1) * 16 + (cc & 1) * 4 + (mi >> 1) * 8 + (rr & 1)) * 64 + (mi & 1) * 16;
#pragma unroll
    for (int q = 0; q < 32; q++) {
      const uint32_t aq = a + ((q >> 2) * 32 + (q & 2)) * 64 + (q & 1) * 32;
      if (q < 8) { uint32_t f[4]; ldw(f, aq); sts16(t16_ + V_WO + q * 4096, make_uint4(f[0], f[1], f[2], f[3])); }
      else ldw(w + q * 4 - 32, aq);
    }
  }
  bar_sync(1 + wg, 128);
  if (t7 == 0)
    for (int i = 0; i < 3; i++) {
      mbar_expect_tx(sbar + i * 8, 16384);
      tma2d_ef(stg + i * 16384, &tmWv, fcol, wg * 512 + i * 128, sbar + i * 8);
    }
  if (lane == 0) probe_near(G, 512 + cta * 8 + (tid >> 5), bars + C_NEAR);
  __syncwarp();
#pragma unroll
  for (int j = 0; j < 24; j++) {
    if ((j & 7) == 0) mbar_wait(sbar + (j >> 3) * 8, 1);
    ldw(w + 96 + j * 4, stg + j * 2048 + wt_off);
  }
  mbar_wait(bars + B_RES, 0);
  if (tid == 32) {
    asm volatile("cp.async.bulk.prefetch.L2.global [%0], 32768;" ::"l"(xin + (size_t)(64 + cta) * 16384) : "memory");
    if (cta >= XP) asm volatile("cp.async.bulk.prefetch.L2.global [%0], 32768;" ::"l"(xin + (size_t)cta * 16384) : "memory");
  }
  cluster_sync();
  if (tid == 0) STAMP(1);
  const uint32_t near = pick_near(CS, V_BARS + C_NEAR);
  const uint32_t rdelta = UNI(mapa(sb, rank ^ 1) - sb);
  uint32_t vxo, vmo;
  sts8f(sb + V_TAB + tid * 8, __uint_as_float(sb + V_WV + (tid >> 7) * 16384 + wt_off),
        __uint_as_float(sb + V_VT + (((tid >> 4) & 4) + ((lane & 7) >> 1)) * 768 + (((tid >> 3) & 4) + (lane & 1)) * 16));
  if (tid < 96) sts4f(sb + V_ONE + tid * 4, __uint_as_float(tid < 64 ? ONE2 : 0));
  if (tid < 32) {
    const char* mp = G + ((gm ^ near ^ 4096) + lane * 8);
    sts16(t16_ + V_TB3, make_uint4(plo(mp), phi(mp), plo(mp) ^ 4096, phi(mp)));
  }
  const uint32_t tabo = UNI((sb >> 1) + V_TAB);
  auto TAB = [&](uint32_t t) __attribute__((always_inline)) {
    uint32_t a; asm volatile("{.reg .u32 x; shr.u32 x, %1, 1; add.u32 %0, x, %2;}" : "=r"(a) : "r"(t), "r"(tabo)); return a;
  };
  if (warp == 0) { sts16(bars + C_T, make_uint4(0, 0, d.u0, d.m0)); }
  auto fetch_x = [&](int n, int h) __attribute__((always_inline)) {
    if (n > 0) wait_ft(bars + C_XE + h * 8, (n - 1) & 1);
    expect(bars + C_XF + h * 8, 32768);
    issue_x(&tmX, sb + V_X + h * 32768 + rank * (32768 / CS), bars + C_XF + h * 8, n, h * 8 + rank * (8 / CS), ALL);
  };
  auto release_x = [&](int h) __attribute__((always_inline)) { arrive_all(CS, t16_, V_BARS + C_XE + h * 8); };
  auto fetch_mem = [&](uint32_t slot) __attribute__((always_inline)) { fetch_mem_mc<CS>(sb + V_MEM, G, near + slot, rank, bars + C_M); };
  auto fetch_ex = [&](int n) __attribute__((always_inline)) {
    {
      if (n > 0) wait_ft(bars + C_EXE, (n - 1) & 1);
      expect(bars + C_EX, EX_BYTES);
      const char* src = reinterpret_cast<const char*>(g_rings.ex[n & 3]) + head * EX_BYTES;
      const uint32_t dst = sb + V_EX;
      if (r != head >> 4) { }
      else if (rank < 2) bulk_mc<3>(dst, src, EX_BYTES, bars + C_EX);
      else if (rank < 4) bulk_mc<12>(dst, src, EX_BYTES, bars + C_EX);
      else if (rank < 6) bulk_mc<48>(dst, src, EX_BYTES, bars + C_EX);
      else bulk_mc<192>(dst, src, EX_BYTES, bars + C_EX);
    }
    __syncwarp();
  };
  auto release_ex = [&]() __attribute__((always_inline)) {
    BASES();
    if ((t16 & 0x1E0) == 0) mbar_arrive_cluster(mapa(SB0 + V_BARS + C_EXE, ((t16 >> 4) & 1) ^ rank));
    __syncwarp();
  };
  auto vproj1 = [&](int n, GemvV& gv, uint32_t ws) __attribute__((always_inline)) {
    float d[16];
    wait_ft(bars + C_XF + 8, n & 1);
    bar_sync(6, 160);
    gv.prefetch(ws);
    WG_FENCE();
#pragma unroll
    for (int k = 0; k < XV; k++) {
      const uint64_t b = cdesc(0, V_X + 32768 + xk(k));
      if (k == 0) wg_rs32<0>(d, w + 96, b);
      else if (k < 24) wg_rs32<1>(d, w + 96 + k * 4, b);
      else wg_rs32<1>(d, gv.pp[(k - 24) >> 1] + (k & 1) * 4, b);
    }
    WG_COMMIT();
    WG_WAIT(0);
    acc_fence16(d);
#pragma unroll
    for (int i = 0; i < 4; i++) sts16f(t16_ + (V_X + 32768 - 2048) + i * 2048, d[4 * i], d[4 * i + 1], d[4 * i + 2], d[4 * i + 3]);
  };
  auto vproj0 = [&](int n, auto mid, auto last) __attribute__((always_inline)) {
    float d[16];
#pragma unroll
    for (int i = 0; i < 4; i++) {
      const float4 p = lds16f(t16_ + V_X + 32768 + i * 2048);
      d[4 * i] = p.x; d[4 * i + 1] = p.y; d[4 * i + 2] = p.z; d[4 * i + 3] = p.w;
    }
    acc_fence16(d);
    WG_FENCE();
#pragma unroll
    for (int kk = 0; kk < XV; kk++) {
      const int k = (kk + SSF) & 31;
      const uint64_t b = cdesc(0, V_X + xk(k));
      if (k < 24) wg_rs32<1>(d, w + 96 + k * 4, b);
      else wg_ss32(d, cdesc(0, V_WV + (k - 24) * 2048), b);
    }
    WG_COMMIT();
    if (w4) release_x(1);
    mid();
    BASES();
    const uint32_t vt = lds4(TAB(t16) + 4) + (n & 3) * 6144 + (t16 & 384);
    const uint32_t tx = (~n & 2) << 15;
    WG_WAIT(0);
    acc_fence16(d);
    const uint4 f0 = make_uint4(pack_tag(d[0], d[1], tx), pack_bf16(d[4], d[5]), pack_bf16(d[8], d[9]), pack_bf16(d[12], d[13]));
    const uint4 f1 = make_uint4(pack_tag(d[2], d[3], tx), pack_bf16(d[6], d[7]), pack_bf16(d[10], d[11]), pack_bf16(d[14], d[15]));
    char* dst = ptr64(t16 + (vxo + (n & 1) * 16384), phi(G));
    st_tagged16(dst, f0); st_tagged16(dst + 512, f1);
    last();
    if (ATT) { stsm4(vt + (clk32() & zero), pack_bf16(d[0], d[1]), f0.y, f0.z, f0.w); stsm4(vt + 32, pack_bf16(d[2], d[3]), f1.y, f1.z, f1.w); }
    release_x(0);
  };
  auto attention = [&](int n, bool gate) __attribute__((always_inline)) {
    float sa[20];
    WG_FENCE();
#pragma unroll
    for (int k = 0; k < 8; k++) {
      const int o = V_EX + (k >> 2) * EX_CTA;
      const uint64_t da = ndesc(0, o + (k & 3) * 1024, 128, 128), db = ndesc(0, o + EX_K + (k & 3) * 1280, 640, 128);
      if (k == 0) wg_ss40<0>(sa, da, db); else wg_ss40<1>(sa, da, db);
    }
    WG_COMMIT();
    BASES();
    const int row = (int)(((t16 - SB0) >> 6) & 31);
    const int dlt = row - (int)((t16 >> 3) & 6);
    WG_WAIT(0);
    asm volatile("" : ACC8(sa, 0), ACC8(sa, 8), "+f"(sa[16]), "+f"(sa[17]), "+f"(sa[18]), "+f"(sa[19])::"memory");
    release_ex();
    float sc[10];
#pragma unroll
    for (int i = 0; i < 8; i++) sc[i] = dlt >= (i >> 1) * 8 + (i & 1) ? sa[(i >> 1) * 4 + (i & 1)] * SCL : -INFINITY;
    sc[8] = sa[16] * SCL; sc[9] = sa[17] * SCL;
    exp10v(sc);
    uint32_t p[5];
#pragma unroll
    for (int i = 0; i < 5; i++) p[i] = pack_bf16(sc[2 * i], sc[2 * i + 1]);
    float o[32];
    const uint32_t z = (n & 3) * 384;
    const uint32_t j0 = junk(), j1 = junk(), j2 = junk(), j3 = junk(), j4 = junk(), j5 = junk();
    uint32_t p5 = p[4];
    keep32(p5);
    float os[4];
    if (PVG && gate) bar_sync(7, 160);
    WG_FENCE();
    wg_rs64<0>(o, p[0], j0, p[1], j1, ndesc(z, V_VT, 128, 768));
    wg_rs8<0>(os, p[0], j0, p[1], j1, ndesc(0, V_ONE, 128, 128));
    wg_rs64<1>(o, p[2], j2, p[3], j3, ndesc(z, V_VT + 256, 128, 768));
    wg_rs8<1>(os, p[2], j2, p[3], j3, ndesc(0, V_ONE, 128, 128));
    wg_rs64<1>(o, p[4], j4, p5, j5, ndesc(z, V_VT + 512, 128, 768));
    wg_rs8<1>(os, p[4], j4, p5, j5, ndesc(0, V_ONE + 128, 128, 128));
    WG_COMMIT();
    WG_WAIT(0);
    asm volatile("" : ACC8(o, 0), ACC8(o, 8), ACC8(o, 16), ACC8(o, 24)::"memory");
    asm volatile("" : "+f"(os[0]), "+f"(os[1]), "+f"(os[2]), "+f"(os[3])::"memory");
    const float inv = rcp_fast(os[0]);
    asm volatile("cp.async.bulk.wait_group.read 0;" ::: "memory");
    __syncwarp();
    const uint32_t oa = sb + V_OUT + row * 128 + (((t16 & 48) ^ (row << 4)) & 0x70);
    sts16(oa, make_uint4(pack_bf16(o[0] * inv, o[1] * inv), pack_bf16(o[4] * inv, o[5] * inv), pack_bf16(o[8] * inv, o[9] * inv), pack_bf16(o[12] * inv, o[13] * inv)));
    sts16(oa ^ 64, make_uint4(pack_bf16(o[16] * inv, o[17] * inv), pack_bf16(o[20] * inv, o[21] * inv), pack_bf16(o[24] * inv, o[25] * inv), pack_bf16(o[28] * inv, o[29] * inv)));
  };
  auto store_o = [&](int n) __attribute__((always_inline)) {
    asm volatile(ELECT "cp.async.bulk.tensor.2d.global.shared::cta.bulk_group [%0, {%2, %3}], [%1];}"
                 ::"l"(&tmU), "r"(sb + (V_OUT - 4096) - wofs * 2), "r"(fcol), "r"((n & 127) * SEG + w4 * 8) : "memory");
    asm volatile("cp.async.bulk.commit_group;" ::: "memory");
  };
  if (warp == 2) fetch_x(0, 1);
  if (tid == 32) mbar_expect_tx(bars + B_PAIR, 512);
  __syncthreads();
  GemvV gv;
  auto reader_side = [&]() __attribute__((always_inline)) {
    uint32_t q;
    for (int it = 0; __any_sync(~0u, (q = ld_relaxed4(&g_rings.side[cta]) - lds4(bars + C_NEAR + 8)) > 1) && it < POLL_LIMIT; it++) { }
    vxo = UNI(plo(G) + (wpage(cta) ^ (q << 12)) + VX0 - wofs - sb);
    vmo = UNI(plo(G) + ((wpage(L_VM + head) ^ (q << 12)) + r * 2048) - (sb >> 1));
  };
  auto gemv_v = [&](int s, auto wg_c) __attribute__((always_inline)) {
    constexpr int wg = decltype(wg_c)::value;
    const uint32_t tg = (s & 1) << 16;
    uint32_t tv;
    gemv_mem<wg, V_MEM, false>(gv, w, s, t16_, wofs, near, G, [&](uint32_t t) __attribute__((always_inline)) { return TAB(t); }, bars + C_M, zero, trc,
                         [&](auto nc, bool) __attribute__((always_inline)) { if (decltype(nc)::value == 26) tv = lds4v(TAB(t16_ | (gv.m[14].x & zero)) + 4); });
#pragma unroll
    for (int i = 0; i < 4; i++) gv.a[i] = (gv.a[i] + gv.b[i]) + (gv.a2[i] + gv.b2[i]);
    const uint32_t m0 = pack_tag(gv.a[0], gv.a[1], tg ^ TAG), m1 = pack_bf16(gv.a[2], gv.a[3]);
    BASES();
    st_tagged8(ptr64(((t16 >> 1) + vmo), phi(G)), m0, m1);
    if (ATT) {
      const uint32_t vt = tv + (s & 3) * 6144 + (512 + wg * 128) + ((t16 >> 2) & 32);
      asm volatile("stmatrix.sync.aligned.m8n8.x2.shared.b16 [%0], {%1, %2};" ::"r"(vt), "r"(pack_bf16(gv.a[0], gv.a[1])), "r"(m1) : "memory");
    }
    TR(1);
    bar_sync(4, 256);
  };
  uint32_t w0[32], wsv;
  auto pre_o = [&]() __attribute__((always_inline)) {
#pragma unroll
    for (int i = 0; i < 8; i++) { const uint4 t = lds16v(t16_ + V_WO + i * 4096); w0[4 * i] = t.x; w0[4 * i + 1] = t.y; w0[4 * i + 2] = t.z; w0[4 * i + 3] = t.w; }
  };
  auto gemv_o = [&](int s, auto wg_c, auto look) __attribute__((always_inline)) {
    constexpr int wg = decltype(wg_c)::value;
    const uint32_t tu = (~s & 1) << 16;
    float a0[4], a1[4], a2[4], a3[4];
    uint4 uv[8];
    auto mul = [&](auto hook) __attribute__((always_inline)) {
#pragma unroll
      for (int i = 0; i < 8; i++) {
        const uint32_t* p = i < 2 ? w0 + 16 : w + (i * 16 - 32);
        if (i == 0) { MMA_XZ(a0, w0, uv[0].x, uv[0].y); MMA_XZ(a1, w0 + 4, uv[0].x, uv[0].y); MMA_XZ(a2, w0 + 8, uv[0].z, uv[0].w); MMA_XZ(a3, w0 + 12, uv[0].z, uv[0].w); }
        else { MMA_X(a0, p, uv[i].x, uv[i].y); MMA_X(a1, p + 4, uv[i].x, uv[i].y); MMA_X(a2, p + 8, uv[i].z, uv[i].w); MMA_X(a3, p + 12, uv[i].z, uv[i].w); }
        hook(i);
      }
    };
    BASES();
    const uint32_t ub = t16 + (V_U + wofs * -7);
    const uint32_t owr = (t16 & 48) * 16 + ((((t16 >> 2) & 0x60) ^ (t16 & 16) ^ ((t16 & 32) * 2)) | ((t16 >> 3) & 8)) + (sb + V_U + wofs * -8);
    landed(zero & owr & w0[0] & w0[4] & w0[8] & w0[12] & w0[16] & w0[20] & w0[24] & w0[28]);
    wait_ft(bars + C_U + wg * 8, s & 1);
    TR(4);
#pragma unroll
    for (int i = 0; i < OLA; i++) uv[i] = lds16v(ub + i * 512);
    uint32_t cc = 0;
    mul([&](int i) __attribute__((always_inline)) {
      cc |= uv[i].x ^ tu;
      if (i + OLA < 8) uv[i + OLA] = lds16v(ub + (i + OLA) * 512);
      if (i + OLA == 7) wsv = lds4v(TAB(t16));
      if (i == 3) look(uv[3].y & zero);
    });
    const bool bad = __any_sync(~0u, (int)(cc << 15) < 0);
    if (__builtin_expect(bad, 0)) {
      CNT(3);
      const char* src = G + ((wpage(L_U + r * 8 + warp) ^ near) + (t16 & 0x1F0));
      for (int it = 0;; it++) {
        uint32_t c2 = 0;
#pragma unroll
        for (int i = 0; i < 8; i++) uv[i] = ld_tagged16(src + i * 512);
#pragma unroll
        for (int i = 0; i < 8; i++) chk2(c2, uv[i], tu);
        if (!__any_sync(~0u, c2 & TAG)) break;
        if (it > POLL_LIMIT) FAIL(4000);
      }
#pragma unroll
      for (int i = 4; i < 8; i++) sts16(ub + i * 512, uv[i]);
      pre_o();
      mul([&](int i) __attribute__((always_inline)) { if (i < 4) uv[i + 4] = lds16v(ub + (i + 4) * 512); });
    }
    sts8f(owr, a0[0] + a2[0], a0[2] + a2[2]); sts8f(owr + 128, a0[1] + a2[1], a0[3] + a2[3]);
    sts8f(owr ^ 16, a1[0] + a3[0], a1[2] + a3[2]); sts8f((owr ^ 16) + 128, a1[1] + a3[1], a1[3] + a3[3]);
  };
  if (wg == 0) {
    if (w4 == 1) bar_arrive(6, 160);
    if (w4 == 0) { expect(bars + C_M, 16384); start_wait(bars + C_NEAR + 8); fetch_mem(16384); }
    reader_side();
    wait_ft(bars + C_XF, 0);
    bar_sync(4, 256);
#pragma unroll 1
    for (int s = UNI(zero - 1);;) {
      const int s1 = UNI(s + 1), ro = s < 0 ? 4 : w4;
      uint32_t tu = 0;
      auto do_u = [&](auto t_c) __attribute__((always_inline)) {
        constexpr int t = decltype(t_c)::value;
        auto fetch_u = [&](auto r_c) __attribute__((always_inline)) {
          constexpr int r = decltype(r_c)::value;
          spin_until(tu, 0);
          TR(12);
#pragma unroll
          for (int i = 0; i < 8 / CS; i++) {
            const int j = (rank >> 1) * (8 / CS) + i;
            const char* src = G + ((wpage(L_U + r * 8 + t * 4) ^ near) + ((j & 1) << 18) + ((j & 2) << 19));
            if (CS > 2) bulk_mc<(0x55u << r) & ALL>(sb + V_U + t * 16384 + j * 4096, src, 4096, bars + C_U + t * 8);
            else bulk(sb + V_U + t * 16384 + j * 4096, src, 4096, bars + C_U + t * 8);
          }
        };
        if (r) fetch_u(IntC<1>()); else fetch_u(IntC<0>());
      };
      vproj0(s + 1, [&]() __attribute__((always_inline)) {
        if (w4 == 2 && s + 2 < NSEG) fetch_x(s + 2, 1);
        if (ro == 2) { expect(bars + C_M, 16384); expect(bars + C_U, 16384); expect(bars + C_U + 8, 16384); }
        if (ro & 1) {
          tu = lds4(bars + C_T + 4);
          if (s == 0) { const char* fl = flag_ptr(G, near, t16_, 0); tu = last_stores(ld_relaxed16(fl), fl, 0).x; }
          LOGT(lds16(bars + C_T));
          tu += (ro == 1 ? d.s : 0) - time_offset(t16_ & zero);
        }
        if (PVG && ro == 0) bar_arrive(7, 160);
      }, [&]() __attribute__((always_inline)) { TR(2); if (ro == 3) do_u(IntC<1>()); });
      if (s < 0) {
        if (w4 == 1) bar_arrive(6, 160);
        wsv = lds4(TAB(t16_));
      } else {
      pre_o();
      if (w4 == 1) do_u(IntC<0>());
      uint4 f = make_uint4(0, 0, 0, 0);
      const char* fl = flag_ptr(G, near, t16_, s);
      gemv_o(s, IntC<0>(), [&](uint32_t z) __attribute__((always_inline)) { ld_relaxed16_if(f, ptr64(plo(fl) | z, phi(fl)), w4 == 0); });
      TR(5);
      BASES();
      const uint32_t tp = (r ^ 1) * 4 + w4;
      const uint32_t ra = (((t16 >> 2) & 0x7C) ^ ((tp & 2) << 3) ^ ((tp & 4) << 4)) + (sb + V_U + tp * 128);
      bar_sync(3, 256);
      {
        float p[8];
#pragma unroll
        for (int i = 0; i < 8; i++) p[i] = lds4f(ra + i * 4096);
        st_async4((t16 >> 2) + (sb - (sb >> 2) + V_RB + rdelta), (((p[0] + p[1]) + (p[2] + p[3])) + (p[4] + p[5])) + (p[6] + p[7]), bars + B_PAIR + rdelta);
      }
      TR(6);
      if (w4 == 1) {
        const uint32_t rb = ((t16 & 0x1F0) ^ ((t16 >> 4) & 16) ^ (r << 6)) + (sb + V_U + r * 512);
        float4 p[8];
#pragma unroll
        for (int i = 0; i < 8; i++) p[i] = lds16fv(rb + i * 4096);
        uint4 t3 = lds16v(t16 + (V_TB3 - 512));
        bar_arrive(6, 160);
        HERE(t3.z);
        float sm[4];
        sm[0] = ((p[0].x + p[1].x) + (p[2].x + p[3].x)) + ((p[4].x + p[5].x) + (p[6].x + p[7].x));
        sm[1] = ((p[0].y + p[1].y) + (p[2].y + p[3].y)) + ((p[4].y + p[5].y) + (p[6].y + p[7].y));
        sm[2] = ((p[0].z + p[1].z) + (p[2].z + p[3].z)) + ((p[4].z + p[5].z) + (p[6].z + p[7].z));
        sm[3] = ((p[0].w + p[1].w) + (p[2].w + p[3].w)) + ((p[4].w + p[5].w) + (p[6].w + p[7].w));
        wait_ft(bars + B_PAIR, s & 1);
        TR(7);
        const float4 q = lds16f(t16_ + (V_RB - 512));
        const uint32_t m0 = pack_tag(sm[0] + q.x, sm[2] + q.z, (~s & 1) << 16), m1 = pack_bf16(sm[1] + q.y, sm[3] + q.w);
        st_tagged8(ptr64(t3.x, t3.y), m0, m1);
        st_tagged8(ptr64(t3.z, t3.w), m0, m1);
        TR(8);
        const uint32_t c0 = clk32();
        if (PF0 == 3) bar_arrive(9, 96);
        st_relaxed4_if(G + ((wpage(L_FLAG) ^ ((t16 & 16) << 8)) + ((~s & 1) * 512 + head * 16 + 8 + r * 4)),
                       ((c0 * 5 + time_offset(t16_ & zero)) & ~31u) | ((s + 1) & 31), (t16 & 0x1E0) == 0);
        expect(bars + B_PAIR, 512);
      }
      if (w4 == 0) {
        const uint4 pl = next_plan(lds16(bars + C_T), last_stores(f, flag_ptr(G, near, t16_, s), s), s, d);
        sts16(bars + C_T, pl);
        const uint32_t tk = approach(pl.x, t16_ & zero);
        TRK(tk);
        spin_until(pl.x, tk);
        TR(9);
        fetch_mem(0);
      } else if (w4 == 2) {
        if (ATT && s >= 1) fetch_ex(s - 1);
      }
      if (PF0 == 3 && w4 >= 2) bar_sync(9, 96);
      }
      gv.prefetch(wsv);
      if (s >= 0) TRD(64 + cta);
      s = s1;
      if (s < NSEG - 1) wait_ft(bars + C_XF, (s + 1) & 1);
      if (ATT && s >= 2) wait_ft(bars + C_EX, s & 1);
      gemv_v(s, IntC<0>());
      if (s == NSEG - 1) break;
    }
  } else {
    wsv = lds4(TAB(t16_));
    vmo = 0;
#pragma unroll 1
    for (int s = UNI(zero - 2);;) {
      const int s1 = UNI(s + 1);
      if (w4 == 2 && s + 2 < NSEG) fetch_x(s + 2, 0);
      if (s + 2 < NSEG) vproj1(s + 2, gv, wsv); else { bar_sync(6, 160); gv.prefetch(wsv); }
      if (ATT) store_o(s - 2);
      TR(7);
      if (s >= 0) TRD(64 + cta);
      s = s1;
      if (s < 0) {
        bar_arrive(4, 256);
        reader_side();
        wsv = lds4(TAB(t16_));
        continue;
      }
      gemv_v(s, IntC<1>());
      if (s == NSEG - 1) break;
      if (ATT && s >= 2) attention(s - 2, true); else if (PVG) bar_sync(7, 160);
      pre_o();
      TR(2);
      gemv_o(s, IntC<1>(), [](uint32_t) {});
      TR(5);
      bar_arrive(3, 256);
      if (ATT) asm volatile("fence.proxy.async.shared::cta;" ::: "memory");
    }
  }
  if (ATT) {
    asm volatile("fence.proxy.async.shared::cta;" ::: "memory");
    __syncthreads();
#pragma unroll 1
    for (int n = NSEG - 3; n < NSEG; n++) {
      if (warp == 1 && n > NSEG - 3) {
        const char* fl = flag_ptr(G, near, t16_, NSEG - 1);
        last_stores(ld_relaxed16(fl), fl, NSEG - 1);
        fetch_ex(n);
      }
      if (wg) {
        wait_ft(bars + C_EX, n & 1);
        attention(n, false);
        asm volatile("fence.proxy.async.shared::cta;" ::: "memory");
        __syncwarp();
        store_o(n);
      }
    }
  }
  if (wg) {
    asm volatile("cp.async.bulk.wait_group 0;" ::: "memory");
    __syncwarp();
    if (lane == 0) { __threadfence(); atomicAdd(&g_rings.ctr[3][0], 1); }
  }
  __syncwarp();
  cluster_sync();
  if (tid == 0) STAMP(2);
}
template <int CS>
__global__ void __launch_bounds__(256, 1)
vo_kernel(const __grid_constant__ CUtensorMap tmWv, const __grid_constant__ CUtensorMap tmWo, const __grid_constant__ CUtensorMap tmX,
          const __grid_constant__ CUtensorMap tmU, const bf16* __restrict__ mem0, const bf16* __restrict__ xin, char* __restrict__ G, const Pace d, int zero) {
  vo_body<CS>(tmWv, tmWo, tmX, tmU, mem0, xin, G, d, zero, blockIdx.x);
}

__device__ uint32_t g_z1[512 * S_LEN];
__device__ uint32_t g_z2[512 * S_LEN];
__device__ __align__(16) uint32_t g_wt[513 * S_LEN];

__device__ __forceinline__ float2 cmul(float2 a, float2 b) { return make_float2(fmaf(a.x, b.x, -a.y * b.y), fmaf(a.x, b.y, a.y * b.x)); }
__device__ __forceinline__ float2 unpack_bf16(uint32_t v) { return make_float2(__uint_as_float(v << 16), __uint_as_float(v & 0xFFFF0000u)); }
__host__ __device__ constexpr float cos32(int i) {
  return i == 0 ? 1.f : i == 1 ? 0.98078528040323044913f : i == 2 ? 0.92387953251128675613f : i == 3 ? 0.83146961230254523708f
       : i == 4 ? 0.70710678118654752440f : i == 5 ? 0.55557023301960222474f : i == 6 ? 0.38268343236508977173f
       : i == 7 ? 0.19509032201612826785f : 0.f;
}
template <int I, int DIR> __device__ __forceinline__ float2 rot32(float2 v) {
  if constexpr (I == 0) return v;
  else if constexpr (I == 8) return DIR > 0 ? make_float2(-v.y, v.x) : make_float2(v.y, -v.x);
  else {
    constexpr float cs = I < 8 ? cos32(I) : -cos32(16 - I);
    constexpr float sn = (I < 8 ? cos32(8 - I) : cos32(I - 8)) * DIR;
    if constexpr (I == 4 || I == 12) {
      constexpr float sgn = (cs > 0) == (sn > 0) ? 1.f : -1.f;
      return make_float2(cs * (v.x - sgn * v.y), cs * (v.y + sgn * v.x));
    } else return make_float2(fmaf(v.x, cs, -v.y * sn), fmaf(v.x, sn, v.y * cs));
  }
}
template <int N, int DIR, int K> struct Comb {
  static __device__ __forceinline__ void run(const float2* e, const float2* o, float2* out) {
    if constexpr (K < N / 2) {
      const float2 t = rot32<K * (32 / N), DIR>(o[K]);
      out[K] = make_float2(e[K].x + t.x, e[K].y + t.y);
      out[K + N / 2] = make_float2(e[K].x - t.x, e[K].y - t.y);
      Comb<N, DIR, K + 1>::run(e, o, out);
    }
  }
};
template <int N, int DIR, int ST> __device__ __forceinline__ void fft_r(const float2* in, float2* out) {
  if constexpr (N == 1) out[0] = in[0];
  else {
    float2 e[N / 2], o[N / 2];
    fft_r<N / 2, DIR, ST * 2>(in, e);
    fft_r<N / 2, DIR, ST * 2>(in + ST, o);
    Comb<N, DIR, 0>::run(e, o, out);
  }
}
template <int N, int DIR> __device__ __forceinline__ void fft_reg(float2* v) {
  float2 t[N];
  fft_r<N, DIR, 1>(v, t);
#pragma unroll
  for (int i = 0; i < N; i++) v[i] = t[i];
}
template <int N> __device__ __forceinline__ void twiddle(float2* v, float x) {
  float2 p[N];
  sincospif(x, &p[1].y, &p[1].x);
#pragma unroll
  for (int k = 2; k < N; k++) p[k] = cmul(p[k / 2], p[k - k / 2]);
#pragma unroll
  for (int k = 1; k < N; k++) v[k] = cmul(v[k], p[k]);
}

constexpr int F1_LD = 16 * 33 - 1;
constexpr int F1_SMEM = 16 * F1_LD * 8;
__device__ __forceinline__ void fft_rows_fwd(float2* fs, int item, const bf16* __restrict__ x, const bf16* __restrict__ wr, const bf16* __restrict__ wi) {
  const int tid = threadIdx.x, s0 = item * 16;
  {
    const int row = tid >> 4, t = tid & 15;
    const uint2* src = reinterpret_cast<const uint2*>(x + (size_t)(s0 + row) * DM) + t;
    float2 a[16], b[16];
#pragma unroll
    for (int i = 0; i < 16; i++) { const uint2 v = __ldg(src + i * 16); a[i] = unpack_bf16(v.x); b[i] = unpack_bf16(v.y); }
    fft_reg<16, -1>(a); twiddle<16>(a, -(float)(2 * t) / 256.f);
    float2* d = fs + row * F1_LD + t;
#pragma unroll
    for (int i = 0; i < 16; i++) d[i * 33] = a[i];
    fft_reg<16, -1>(b); twiddle<16>(b, -(float)(2 * t + 1) / 256.f);
#pragma unroll
    for (int i = 0; i < 16; i++) d[i * 33 + 16] = b[i];
  }
  __syncthreads();
  {
    const int row = tid & 15, k2 = tid >> 4;
    float2 v[32];
#pragma unroll
    for (int i = 0; i < 32; i++) v[i] = fs[row * F1_LD + k2 * 33 + (i >> 1) + (i & 1) * 16];
    fft_reg<32, -1>(v);
#pragma unroll
    for (int i = 0; i < 32; i++) g_z1[(k2 + 16 * i) * S_LEN + s0 + row] = pack_bf16(v[i].x, v[i].y);
  }
  {
    __syncthreads();
    uint4* sw = reinterpret_cast<uint4*>(fs);
    const uint4* pr = reinterpret_cast<const uint4*>(wr + (size_t)s0 * 513);
    const uint4* pi = reinterpret_cast<const uint4*>(wi + (size_t)s0 * 513);
#pragma unroll
    for (int q = 0; q < 5; q++) {
      const int i = tid + q * 256;
      if (i < 1026) { sw[i] = __ldg(pr + i); sw[1026 + i] = __ldg(pi + i); }
    }
    __syncthreads();
    const uint16_t* hr = reinterpret_cast<const uint16_t*>(fs) + (tid & 3) * 4 * 513;
    const uint16_t* hi = hr + 1026 * 8;
#pragma unroll
    for (int q = 0; q < 9; q++) {
      const int k = (tid >> 2) + q * 64;
      if (q == 8 && k != 512) break;
      uint32_t o[4];
#pragma unroll
      for (int r = 0; r < 4; r++) o[r] = (uint32_t)hr[r * 513 + k] | ((uint32_t)hi[r * 513 + k] << 16);
      *reinterpret_cast<uint4*>(g_wt + k * S_LEN + s0 + (tid & 3) * 4) = make_uint4(o[0], o[1], o[2], o[3]);
    }
  }
}

constexpr int F2_LD = 2048 + 128;
__device__ __forceinline__ int f2_pad(int i) { return i + (i >> 7); }
__device__ __forceinline__ void fft_cols(float2* fs, int item) {
  const int tid = threadIdx.x, half = tid >> 7, t = tid & 127;
  const int k = item == 0 ? half * 256 : (half ? 512 - item : item);
  float2* my = fs + half * F2_LD;
  const float2* mir = fs + (item == 0 ? half : half ^ 1) * F2_LD;
  float2 v[16];
#pragma unroll
  for (int a = 0; a < 16; a++) v[a] = unpack_bf16(__ldcg(&g_z1[k * S_LEN + t + 128 * a]));
  fft_reg<16, -1>(v); twiddle<16>(v, -(float)t / 1024.f);
#pragma unroll
  for (int i = 0; i < 16; i++) my[f2_pad(i * 128 + t)] = v[i];
  bar_sync(1 + half, 128);
  const int t0 = t & 15, kp = t >> 4;
#pragma unroll
  for (int h = 0; h < 2; h++) {
#pragma unroll
    for (int b = 0; b < 8; b++) v[h * 8 + b] = my[f2_pad((2 * kp + h) * 128 + t0 + 16 * b)];
    fft_reg<8, -1>(v + h * 8);
  }
  float2 p8[8];
  sincospif(-(float)t0 / 64.f, &p8[1].y, &p8[1].x);
#pragma unroll
  for (int i = 2; i < 8; i++) p8[i] = cmul(p8[i / 2], p8[i - i / 2]);
#pragma unroll
  for (int h = 0; h < 2; h++)
#pragma unroll
    for (int b = 0; b < 8; b++)
      my[f2_pad((2 * kp + h) * 128 + t0 + 16 * b)] = b ? cmul(v[h * 8 + b], p8[b]) : v[h * 8];
  uint32_t wa[16], wb[16];
#pragma unroll
  for (int m = 0; m < 16; m++) {
    wa[m] = __ldcg(&g_wt[k * S_LEN + t + 128 * m]);
    wb[m] = __ldcg(&g_wt[(512 - k) * S_LEN + ((2048 - t - 128 * m) & 2047)]);
  }
  bar_sync(1 + half, 128);
  const int base3 = (t & 15) * 128 + (t >> 4) * 16;
#pragma unroll
  for (int i = 0; i < 16; i++) v[i] = my[f2_pad(base3 + i)];
  fft_reg<16, -1>(v);
  bar_sync(1 + half, 128);
#pragma unroll
  for (int m = 0; m < 16; m++) my[t + 128 * m] = v[m];
  __syncthreads();
  {
    float sn, cs;
    sincospif((float)k / 512.f, &sn, &cs);
    const float sc = 0.5f / (2048.f * 512.f);
#pragma unroll
    for (int m = 0; m < 16; m++) {
      const int j = t + 128 * m, jm = (2048 - j) & 2047;
      float2 A = unpack_bf16(wa[m]), B = unpack_bf16(wb[m]);
      B.y = -B.y;
      if (k == 0) {
        const float2 A2 = unpack_bf16(__ldcg(&g_wt[jm])), B2 = unpack_bf16(__ldcg(&g_wt[512 * S_LEN + j]));
        A = make_float2(0.5f * (A.x + A2.x), 0.5f * (A.y - A2.y));
        B = make_float2(0.5f * (B.x + B2.x), 0.5f * (B.y + B2.y));
      }
      const float2 df = make_float2((A.x - B.x) * sc, (A.y - B.y) * sc);
      const float2 ca = make_float2(fmaf(-sn, df.x, (A.x + B.x) * sc), fmaf(-sn, df.y, (A.y + B.y) * sc));
      const float2 cb = make_float2(-cs * df.y, cs * df.x);
      float2 zc = mir[jm];
      zc.y = -zc.y;
      const float2 r1 = cmul(ca, v[m]), r2 = cmul(cb, zc);
      v[m] = make_float2(r1.x + r2.x, r1.y + r2.y);
    }
  }
  fft_reg<16, 1>(v);
  __syncthreads();
#pragma unroll
  for (int i = 0; i < 16; i++) my[f2_pad(base3 + i)] = v[i];
  bar_sync(1 + half, 128);
#pragma unroll
  for (int h = 0; h < 2; h++) {
#pragma unroll
    for (int b = 0; b < 8; b++) {
      const float2 z = my[f2_pad((2 * kp + h) * 128 + t0 + 16 * b)];
      v[h * 8 + b] = b ? cmul(z, make_float2(p8[b].x, -p8[b].y)) : z;
    }
    fft_reg<8, 1>(v + h * 8);
#pragma unroll
    for (int b = 0; b < 8; b++) my[f2_pad((2 * kp + h) * 128 + t0 + 16 * b)] = v[h * 8 + b];
  }
  bar_sync(1 + half, 128);
#pragma unroll
  for (int i = 0; i < 16; i++) v[i] = my[f2_pad(i * 128 + t)];
  twiddle<16>(v, (float)t / 1024.f);
  fft_reg<16, 1>(v);
#pragma unroll
  for (int a = 0; a < 16; a++) g_z2[k * S_LEN + t + 128 * a] = pack_bf16(v[a].x, v[a].y);
}

__device__ __forceinline__ void fft_rows_inv(float2* fs, int item, bf16* __restrict__ out) {
  const int tid = threadIdx.x, s0 = item * 16;
  {
    const int row = tid & 15, k2 = tid >> 4;
    float2 v[32];
#pragma unroll
    for (int i = 0; i < 32; i++) v[i] = unpack_bf16(__ldcg(&g_z2[(k2 + 16 * i) * S_LEN + s0 + row]));
    fft_reg<32, 1>(v);
#pragma unroll
    for (int i = 0; i < 32; i++) fs[row * F1_LD + k2 * 33 + (i >> 1) + (i & 1) * 16] = v[i];
  }
  __syncthreads();
  {
    const int row = tid >> 4, t = tid & 15;
    const float2* d = fs + row * F1_LD + t;
    float2 a[16], b[16];
#pragma unroll
    for (int i = 0; i < 16; i++) { a[i] = d[i * 33]; b[i] = d[i * 33 + 16]; }
    twiddle<16>(a, (float)(2 * t) / 256.f); fft_reg<16, 1>(a);
    twiddle<16>(b, (float)(2 * t + 1) / 256.f); fft_reg<16, 1>(b);
    uint2* dst = reinterpret_cast<uint2*>(out + (size_t)(s0 + row) * OUT_LD) + t;
#pragma unroll
    for (int i = 0; i < 16; i++) dst[i * 16] = make_uint2(pack_bf16(a[i].x, a[i].y), pack_bf16(b[i].x, b[i].y));
  }
}

__global__ void __maxnreg__(112) fft_all(const bf16* __restrict__ x, const bf16* __restrict__ wr, const bf16* __restrict__ wi, bf16* __restrict__ out) {
  extern __shared__ float2 fs[];
  volatile int& s_item = *reinterpret_cast<volatile int*>(fs + 15 * F1_LD + 14 * 33 + 32);
  asm volatile("griddepcontrol.launch_dependents;" ::: "memory");
  int* ctr = &g_rings.ctr[0][0];
  int phase = 0, cnt = 0;
  for (;;) {
    __syncthreads();
    if (threadIdx.x == 0) {
      const int it = atomicAdd(ctr, 1) + 1;
      const int ph = (it >= 128) + (it >= 384) + (it >= 512);
      if (ph != phase) {
        if (cnt) { __threadfence(); atomicAdd(ctr + 32 + phase * 32, cnt); }
        const int target = ph == 1 ? 127 : 255;
        for (int i = 0; ph < 3 && i < (1 << 22); i++) {
          int v; asm volatile("ld.acquire.gpu.global.s32 %0, [%1];" : "=r"(v) : "l"(ctr + ph * 32) : "memory");
          if (v == target) break;
          __nanosleep(100);
        }
        phase = ph; cnt = 0;
      }
      cnt += ph < 2;
      if (it == 128) STAMP(5);
      if (it == 384) STAMP(6);
      if (it >= 512) STAMP(7);
      s_item = it;
    }
    __syncthreads();
    const int it = s_item;
    if (it >= 512) break;
    if (it < 128) {
      const int nx = it + (int)gridDim.x;
      if (nx < 128) {
        asm volatile("prefetch.global.L2 [%0];" ::"l"(x + (size_t)nx * 16 * DM + threadIdx.x * 64));
        asm volatile("prefetch.global.L2 [%0];" ::"l"((threadIdx.x < 128 ? wr : wi) + (size_t)nx * 16 * 513 + (threadIdx.x & 127) * 64));
      }
      fft_rows_fwd(fs, it, x, wr, wi);
    }
    else if (it < 384) fft_cols(fs, it - 128);
    else fft_rows_inv(fs, it - 384, out);
  }
  if (blockIdx.x == 0) asm volatile("griddepcontrol.wait;" ::: "memory");
}

typedef CUresult (*EncodeFn)(CUtensorMap*, CUtensorMapDataType, cuuint32_t, void*, const cuuint64_t*, const cuuint64_t*,
                             const cuuint32_t*, const cuuint32_t*, CUtensorMapInterleave, CUtensorMapSwizzle,
                             CUtensorMapL2promotion, CUtensorMapFloatOOBfill);
static EncodeFn g_encode;
static bool g_big;
static CUtensorMap make_map(const void* p, uint64_t cols, uint64_t rows, uint64_t ld, uint32_t bc, uint32_t br, bool swz) {
  CUtensorMap m;
  cuuint64_t dims[2] = {cols, rows}, st[1] = {ld * 2};
  cuuint32_t box[2] = {bc, br}, es[2] = {1, 1};
  g_encode(&m, CU_TENSOR_MAP_DATA_TYPE_BFLOAT16, 2, const_cast<void*>(p), dims, st, box, es, CU_TENSOR_MAP_INTERLEAVE_NONE,
           swz ? CU_TENSOR_MAP_SWIZZLE_128B : CU_TENSOR_MAP_SWIZZLE_NONE, CU_TENSOR_MAP_L2_PROMOTION_L2_256B,
           CU_TENSOR_MAP_FLOAT_OOB_FILL_NONE);
  return m;
}
template <typename... KA, typename... A>
static void launch(void (*k)(KA...), dim3 grid, dim3 block, size_t smem, int cluster, bool pdl, cudaStream_t st, A... args) {
  cudaLaunchConfig_t cfg = {};
  cfg.gridDim = grid; cfg.blockDim = block; cfg.dynamicSmemBytes = smem; cfg.stream = st;
  cudaLaunchAttribute at[2]; int n = 0;
  if (cluster > 1) { at[n].id = cudaLaunchAttributeClusterDimension; at[n].val.clusterDim.x = cluster; at[n].val.clusterDim.y = 1; at[n].val.clusterDim.z = 1; n++; }
  if (pdl) { at[n].id = cudaLaunchAttributeProgrammaticStreamSerialization; at[n].val.programmaticStreamSerializationAllowed = 1; n++; }
  cfg.attrs = at; cfg.numAttrs = n;
  cudaLaunchKernelEx(&cfg, k, args...);
}
#define PARAM(n, d) (d)

#define ACS 8
#define VCS 8
extern "C" void kernel_launch(void* const* d_in, const int* in_sizes, int n_in, void* d_out, int out_size) {
  const bf16* Ax = (const bf16*)d_in[0]; const bf16* Awr = (const bf16*)d_in[1]; const bf16* Awi = (const bf16*)d_in[2];
  const bf16* Bx = (const bf16*)d_in[3]; const bf16* mem0 = (const bf16*)d_in[4];
  const bf16* Wq = (const bf16*)d_in[5]; const bf16* Wk = (const bf16*)d_in[6]; const bf16* Wv = (const bf16*)d_in[7];
  const bf16* Wo = (const bf16*)d_in[8];
  bf16* out = (bf16*)d_out;
  if (!g_encode) {
    cudaDriverEntryPointQueryResult qr;
    cudaGetDriverEntryPoint("cuTensorMapEncodeTiled", (void**)&g_encode, cudaEnableDefault, &qr);
    cudaFuncSetAttribute(gemm_kernel, cudaFuncAttributeMaxDynamicSharedMemorySize, G_SMEM);
    cudaFuncSetAttribute(qk_kernel, cudaFuncAttributeMaxDynamicSharedMemorySize, A_SMEM);
    cudaFuncSetAttribute(vo_kernel<VCS>, cudaFuncAttributeMaxDynamicSharedMemorySize, V_SMEM);
    cudaFuncSetAttribute(vo_kernel<2>, cudaFuncAttributeMaxDynamicSharedMemorySize, V_SMEM);
    cudaLaunchConfig_t cfg = {};
    cfg.gridDim = dim3(64); cfg.blockDim = dim3(256); cfg.dynamicSmemBytes = V_SMEM;
    cudaLaunchAttribute at;
    at.id = cudaLaunchAttributeClusterDimension; at.val.clusterDim.x = VCS; at.val.clusterDim.y = 1; at.val.clusterDim.z = 1;
    cfg.attrs = &at; cfg.numAttrs = 1;
    int n = 0;
    g_big = cudaOccupancyMaxActiveClusters(&n, vo_kernel<VCS>, &cfg) == cudaSuccess && n * VCS >= 120;
    cudaFuncSetAttribute(fft_all, cudaFuncAttributeMaxDynamicSharedMemorySize, F1_SMEM);
  }
  void *p_ux, *p_rings, *p_win;
  cudaGetSymbolAddress(&p_ux, g_ux); cudaGetSymbolAddress(&p_rings, g_rings); cudaGetSymbolAddress(&p_win, g_win);
  char* win = (char*)(((uintptr_t)p_win + (2u << 20) - 1) & ~(uintptr_t)((2u << 20) - 1));
  const CUtensorMap rWq = make_map(Wq, HD, DM, HD, 64, 128, true), rWk = make_map(Wk, HD, DM, HD, 64, 128, true),
                    rWv = make_map(Wv, HD, DM, HD, 64, 128, true), rWo = make_map(Wo, DM, HD, DM, 32, 128, false);
  CUtensorMap rX[3];
  for (int i = 0; i < 3; i++) {
    cuuint64_t dims[3] = {64, S_LEN, 16}, st[2] = {DM * 2, 128};
    cuuint32_t box[3] = {64, 32, i == 0 ? 4u : i == 1 ? 8u / VCS : 8u / ACS}, es[3] = {1, 1, 1};
    g_encode(&rX[i], CU_TENSOR_MAP_DATA_TYPE_BFLOAT16, 3, const_cast<bf16*>(Bx), dims, st, box, es, CU_TENSOR_MAP_INTERLEAVE_NONE,
             CU_TENSOR_MAP_SWIZZLE_128B, CU_TENSOR_MAP_L2_PROMOTION_L2_256B, CU_TENSOR_MAP_FLOAT_OOB_FILL_NONE);
  }
  const CUtensorMap mU = make_map(p_ux, HD, S_LEN, HD, 64, 64, true), mWo = make_map(Wo, DM, HD, DM, 64, 64, true);
  const CUtensorMap sU = make_map(p_ux, HD, S_LEN, HD, 64, 8, true);
  const CUtensorMap mOut = make_map(out, OUT_LD, S_LEN, OUT_LD, 64, 64, true);
  cudaStream_t st = cudaStreamPerThread;
  const Pace pace = {5 * PARAM("U0", 2900), 10 * (PARAM("M0", 2200) / 2), 5 * PARAM("MU", 90), 5 * PARAM("MM", 100), 5 * PARAM("DOK", -10), 5 * PARAM("DL", 900),
                     5 * PARAM("DEC", 6), 5 * PARAM("CAP", 60), 5 * PARAM("DS", 200), 5 * PARAM("DC", 800)};
  if (g_big) launch(vo_kernel<VCS>, dim3(64), dim3(256), V_SMEM, VCS, false, st, rWv, rWo, rX[1], sU, mem0, Bx, win, pace, 0);
  else launch(vo_kernel<2>, dim3(64), dim3(256), V_SMEM, 2, false, st, rWv, rWo, rX[0], sU, mem0, Bx, win, pace, 0);
  const int nbig = g_big && ACS > 2 ? 56 : 0;
  if (nbig) launch(qk_kernel, dim3(nbig), dim3(256), A_SMEM, ACS, true, st, rWq, rWk, rX[2], win, pace, 0, 0, ACS);
  launch(qk_kernel, dim3(64 - nbig), dim3(256), A_SMEM, 2, true, st, rWq, rWk, rX[0], win, pace, 0, nbig, 2);
  if (PARAM("BG", 8)) launch(fft_all, dim3(PARAM("BG", 8)), dim3(256), F1_SMEM, 1, true, st, Ax, Awr, Awi, out);
  launch(gemm_kernel, dim3(8, 16), dim3(288), G_SMEM, 2, true, st, mU, mWo, mWo, mWo, mOut, 8, 64, 1024, (const int*)((char*)p_rings + offsetof(Rings, ctr) + 3 * 128));
  if (PARAM("TAIL", 128)) launch(fft_all, dim3(PARAM("TAIL", 128)), dim3(256), F1_SMEM, 1, true, st, Ax, Awr, Awi, out);
}
```

```cpp
#include <cuda_runtime.h>
#include <cuda_bf16.h>
#include <cuda.h>
#include <stdint.h>

typedef __nv_bfloat16 bf16;

constexpr int S_LEN = 2048, DM = 1024, NH = 32, DH = 128, HD = 4096, NMEM = 8, SEG = 32, NSEG = 64;
constexpr int OUT_LD = 2048;
constexpr uint32_t SENT = 0xFFFFFFFFu;

__device__ __forceinline__ uint32_t smem_u32(const void* p) { return (uint32_t)__cvta_generic_to_shared(p); }
__device__ __forceinline__ void mbar_init(uint32_t bar, uint32_t cnt) {
  asm volatile("mbarrier.init.shared::cta.b64 [%0], %1;" ::"r"(bar), "r"(cnt) : "memory");
}
__device__ __forceinline__ void mbar_expect_tx(uint32_t bar, uint32_t bytes) {
  asm volatile("mbarrier.arrive.expect_tx.shared::cta.b64 _, [%0], %1;" ::"r"(bar), "r"(bytes) : "memory");
}
__device__ __forceinline__ void mbar_arrive(uint32_t bar) {
  asm volatile("mbarrier.arrive.shared::cta.b64 _, [%0];" ::"r"(bar) : "memory");
}
__device__ __forceinline__ void mbar_arrive_tx_if(uint32_t bar, uint32_t bytes, uint32_t cond) {
  asm volatile("{.reg .pred q; setp.ne.u32 q, %2, 0; @q mbarrier.arrive.expect_tx.shared::cta.b64 _, [%0], %1;}" ::"r"(bar), "r"(bytes), "r"(cond) : "memory");
}
__device__ __forceinline__ void mbar_arrive_cluster(uint32_t bar_cluster_addr) {
  asm volatile("mbarrier.arrive.shared::cluster.b64 _, [%0];" ::"r"(bar_cluster_addr) : "memory");
}
__device__ __forceinline__ bool mbar_try(uint32_t bar, uint32_t par) {
  uint32_t ok;
  asm volatile("{.reg .pred p; mbarrier.try_wait.parity.shared::cta.b64 p, [%1], %2; selp.u32 %0, 1, 0, p;}"
               : "=r"(ok) : "r"(bar), "r"(par) : "memory");
  return ok;
}
#define FAIL(id) do { asm volatile("trap; exit;"); __builtin_unreachable(); } while (0)
__device__ __forceinline__ void mbar_wait(uint32_t bar, uint32_t par) {
  if (__builtin_expect(!mbar_try(bar, par), 0)) {
    int it = 0;
    while (!mbar_try(bar, par)) { if (++it > (1 << 18)) FAIL((bar & 255) + par * 1000); }
  }
}
__device__ __forceinline__ void tma2d(uint32_t dst, const CUtensorMap* tm, int c0, int c1, uint32_t bar) {
  asm volatile("cp.async.bulk.tensor.2d.shared::cluster.global.mbarrier::complete_tx::bytes [%0], [%1, {%3, %4}], [%2];"
               ::"r"(dst), "l"(tm), "r"(bar), "r"(c0), "r"(c1) : "memory");
}
__device__ __forceinline__ void tma2d_ef(uint32_t dst, const CUtensorMap* tm, int c0, int c1, uint32_t bar) {
  asm volatile("cp.async.bulk.tensor.2d.shared::cluster.global.mbarrier::complete_tx::bytes.L2::cache_hint [%0], [%1, {%3, %4}], [%2], %5;"
               ::"r"(dst), "l"(tm), "r"(bar), "r"(c0), "r"(c1), "l"(0x12F0000000000000ull) : "memory");
}
__device__ __forceinline__ void tma2d_pf(const CUtensorMap* tm, int c0, int c1) {
  asm volatile("cp.async.bulk.prefetch.tensor.2d.L2.global [%0, {%1, %2}];" ::"l"(tm), "r"(c0), "r"(c1) : "memory");
}
__device__ __forceinline__ void tma2d_mc(uint32_t dst, const CUtensorMap* tm, int c0, int c1, uint32_t bar, uint16_t mask) {
  asm volatile("cp.async.bulk.tensor.2d.shared::cluster.global.mbarrier::complete_tx::bytes.multicast::cluster [%0], [%1, {%3, %4}], [%2], %5;"
               ::"r"(dst), "l"(tm), "r"(bar), "r"(c0), "r"(c1), "h"(mask) : "memory");
}
__device__ __forceinline__ void tma2d_store(const CUtensorMap* tm, uint32_t src, int c0, int c1) {
  asm volatile("cp.async.bulk.tensor.2d.global.shared::cta.bulk_group [%0, {%2, %3}], [%1];"
               ::"l"(tm), "r"(src), "r"(c0), "r"(c1) : "memory");
}
__device__ __forceinline__ uint32_t mapa(uint32_t a, uint32_t r) {
  uint32_t o; asm("mapa.shared::cluster.u32 %0, %1, %2;" : "=r"(o) : "r"(a), "r"(r)); return o;
}
__device__ __forceinline__ void st_async8(uint32_t addr, float a, float b, uint32_t bar) {
  asm volatile("st.async.weak.shared::cluster.mbarrier::complete_tx::bytes.v2.f32 [%0], {%1, %2}, [%3];"
               ::"r"(addr), "f"(a), "f"(b), "r"(bar) : "memory");
}
__device__ __forceinline__ void st_async8_if(uint32_t addr, float a, float b, uint32_t bar, uint32_t cond) {
  asm volatile("{.reg .pred q; setp.ne.u32 q, %4, 0; @q st.async.weak.shared::cluster.mbarrier::complete_tx::bytes.v2.f32 [%0], {%1, %2}, [%3];}"
               ::"r"(addr), "f"(a), "f"(b), "r"(bar), "r"(cond) : "memory");
}
__device__ __forceinline__ void st_async16(uint32_t addr, const float* v, uint32_t bar) {
  asm volatile("st.async.weak.shared::cluster.mbarrier::complete_tx::bytes.v4.f32 [%0], {%1, %2, %3, %4}, [%5];"
               ::"r"(addr), "f"(v[0]), "f"(v[1]), "f"(v[2]), "f"(v[3]), "r"(bar) : "memory");
}
__device__ __forceinline__ void st_async4(uint32_t addr, float a, uint32_t bar) {
  asm volatile("st.async.weak.shared::cluster.mbarrier::complete_tx::bytes.f32 [%0], %1, [%2];"
               ::"r"(addr), "f"(a), "r"(bar) : "memory");
}
__device__ __forceinline__ void cluster_sync() {
  asm volatile("barrier.cluster.arrive.release.aligned; barrier.cluster.wait.acquire.aligned;" ::: "memory");
}
__device__ __forceinline__ void cluster_sync_relaxed() {
  __syncthreads();
  asm volatile("barrier.cluster.arrive.relaxed.aligned; barrier.cluster.wait.aligned;" ::: "memory");
}
__device__ __forceinline__ void bar_sync(int id, int n) { asm volatile("bar.sync %0, %1;" ::"r"(id), "r"(n) : "memory"); }
__device__ __forceinline__ void ldsm4(uint32_t& r0, uint32_t& r1, uint32_t& r2, uint32_t& r3, uint32_t a) {
  asm volatile("ldmatrix.sync.aligned.m8n8.x4.shared.b16 {%0,%1,%2,%3}, [%4];"
               : "=r"(r0), "=r"(r1), "=r"(r2), "=r"(r3) : "r"(a) : "memory");
}
__device__ __forceinline__ void ldsm4t(uint32_t& r0, uint32_t& r1, uint32_t& r2, uint32_t& r3, uint32_t a) {
  asm volatile("ldmatrix.sync.aligned.m8n8.x4.trans.shared.b16 {%0,%1,%2,%3}, [%4];"
               : "=r"(r0), "=r"(r1), "=r"(r2), "=r"(r3) : "r"(a) : "memory");
}
__device__ __forceinline__ void stsm4(uint32_t a, uint32_t r0, uint32_t r1, uint32_t r2, uint32_t r3) {
  asm volatile("stmatrix.sync.aligned.m8n8.x4.shared.b16 [%0], {%1,%2,%3,%4};"
               ::"r"(a), "r"(r0), "r"(r1), "r"(r2), "r"(r3) : "memory");
}
__device__ __forceinline__ void stsm1(uint32_t a, uint32_t r0) {
  asm volatile("stmatrix.sync.aligned.m8n8.x1.shared.b16 [%0], {%1};" ::"r"(a), "r"(r0) : "memory");
}
__device__ __forceinline__ void mma16816(float* d, uint32_t a0, uint32_t a1, uint32_t a2, uint32_t a3, uint32_t b0, uint32_t b1) {
  asm volatile("mma.sync.aligned.m16n8k16.row.col.f32.bf16.bf16.f32 {%0,%1,%2,%3}, {%4,%5,%6,%7}, {%8,%9}, {%0,%1,%2,%3};"
               : "+f"(d[0]), "+f"(d[1]), "+f"(d[2]), "+f"(d[3])
               : "r"(a0), "r"(a1), "r"(a2), "r"(a3), "r"(b0), "r"(b1));
}
__device__ __forceinline__ void mma1688(float* d, uint32_t a0, uint32_t a1, uint32_t b0) {
  asm volatile("mma.sync.aligned.m16n8k8.row.col.f32.bf16.bf16.f32 {%0,%1,%2,%3}, {%4,%5}, {%6}, {%0,%1,%2,%3};"
               : "+f"(d[0]), "+f"(d[1]), "+f"(d[2]), "+f"(d[3]) : "r"(a0), "r"(a1), "r"(b0));
}
__device__ __forceinline__ uint32_t pack_bf16(float lo, float hi) {
  uint32_t r; asm("cvt.rn.bf16x2.f32 %0, %1, %2;" : "=r"(r) : "f"(hi), "f"(lo)); return r;
}
__device__ __forceinline__ uint4 ld_relaxed16(const void* p) {
  uint4 v;
  asm volatile("ld.relaxed.gpu.global.v4.u32 {%0,%1,%2,%3}, [%4];" : "=r"(v.x), "=r"(v.y), "=r"(v.z), "=r"(v.w) : "l"(p) : "memory");
  return v;
}
__device__ __forceinline__ uint4 ld_relaxed16b(const void* p) {
  uint4 v;
  asm volatile("ld.relaxed.gpu.global.v4.b32 {%0,%1,%2,%3}, [%4];" : "=r"(v.x), "=r"(v.y), "=r"(v.z), "=r"(v.w) : "l"(p) : "memory");
  return v;
}
__device__ __forceinline__ void ld_relaxed16_if(uint4& v, const void* p, uint32_t cond) {
  asm volatile("{.reg .pred q; setp.ne.u32 q, %5, 0; @q ld.relaxed.gpu.global.v4.u32 {%0,%1,%2,%3}, [%4];}"
               : "+r"(v.x), "+r"(v.y), "+r"(v.z), "+r"(v.w) : "l"(p), "r"(cond) : "memory");
}
__device__ __forceinline__ void ld_relaxed8_if(uint2& v, const void* p, uint32_t cond) {
  asm volatile("{.reg .pred q; setp.ne.u32 q, %3, 0; @q ld.relaxed.gpu.global.v2.u32 {%0,%1}, [%2];}" : "+r"(v.x), "+r"(v.y) : "l"(p), "r"(cond) : "memory");
}
__device__ __forceinline__ uint32_t ld_relaxed4(const void* p) {
  uint32_t v; asm volatile("ld.relaxed.gpu.global.u32 %0, [%1];" : "=r"(v) : "l"(p) : "memory"); return v;
}
__device__ __forceinline__ void st_relaxed4(void* p, uint32_t v) {
  asm volatile("st.relaxed.gpu.global.u32 [%0], %1;" ::"l"(p), "r"(v) : "memory");
}
__device__ __forceinline__ void st_relaxed4_if(void* p, uint32_t v, uint32_t cond) {
  asm volatile("{.reg .pred q; setp.ne.u32 q, %2, 0; @q st.relaxed.gpu.global.u32 [%0], %1;}" ::"l"(p), "r"(v), "r"(cond) : "memory");
}
__device__ __forceinline__ void sts16(uint32_t a, uint4 v) {
  asm volatile("st.shared.v4.u32 [%0], {%1,%2,%3,%4};" ::"r"(a), "r"(v.x), "r"(v.y), "r"(v.z), "r"(v.w) : "memory");
}
__device__ __forceinline__ void sts4f(uint32_t a, float v) { asm volatile("st.shared.f32 [%0], %1;" ::"r"(a), "f"(v) : "memory"); }
__device__ __forceinline__ void sts8f(uint32_t a, float x, float y) { asm volatile("st.shared.v2.f32 [%0], {%1,%2};" ::"r"(a), "f"(x), "f"(y) : "memory"); }
__device__ __forceinline__ float lds4f(uint32_t a) { float v; asm volatile("ld.shared.f32 %0, [%1];" : "=f"(v) : "r"(a) : "memory"); return v; }
__device__ __forceinline__ float2 lds8f(uint32_t a) { float2 v; asm volatile("ld.shared.v2.f32 {%0,%1}, [%2];" : "=f"(v.x), "=f"(v.y) : "r"(a) : "memory"); return v; }
__device__ __forceinline__ uint32_t lds4(uint32_t a) { uint32_t v; asm volatile("ld.shared.u32 %0, [%1];" : "=r"(v) : "r"(a) : "memory"); return v; }
__device__ __forceinline__ uint2 lds8(uint32_t a) { uint2 v; asm volatile("ld.shared.v2.u32 {%0,%1}, [%2];" : "=r"(v.x), "=r"(v.y) : "r"(a) : "memory"); return v; }
__device__ __forceinline__ uint32_t umax4(uint4 v) { return max(max(v.x, v.y), max(v.z, v.w)); }
__device__ __forceinline__ float ex2(float x) { float y; asm("ex2.approx.ftz.f32 %0, %1;" : "=f"(y) : "f"(x)); return y; }

__device__ __forceinline__ void fence_gpu() { asm volatile("fence.acq_rel.gpu;" ::: "memory"); }
#define WG_FENCE() asm volatile("wgmma.fence.sync.aligned;" ::: "memory")
#define WG_COMMIT() asm volatile("wgmma.commit_group.sync.aligned;" ::: "memory")
#define WG_WAIT(n) asm volatile("wgmma.wait_group.sync.aligned " #n ";" ::: "memory")
__device__ __forceinline__ uint64_t mk_desc(uint32_t addr, uint32_t lbo, uint32_t sbo) {
  return (uint64_t)((addr >> 4) & 0x3FFF) | ((uint64_t)(lbo >> 4) << 16) | ((uint64_t)(sbo >> 4) << 32) | ((uint64_t)1 << 62);
}
__device__ __forceinline__ void stsm4t(uint32_t a, uint32_t r0, uint32_t r1, uint32_t r2, uint32_t r3) {
  asm volatile("stmatrix.sync.aligned.m8n8.x4.trans.shared.b16 [%0], {%1,%2,%3,%4};"
               ::"r"(a), "r"(r0), "r"(r1), "r"(r2), "r"(r3) : "memory");
}
__device__ __forceinline__ void sts16f(uint32_t a, float x, float y, float z, float w) {
  asm volatile("st.shared.v4.f32 [%0], {%1,%2,%3,%4};" ::"r"(a), "f"(x), "f"(y), "f"(z), "f"(w) : "memory");
}
__device__ __forceinline__ float4 lds16f(uint32_t a) {
  float4 v; asm volatile("ld.shared.v4.f32 {%0,%1,%2,%3}, [%4];" : "=f"(v.x), "=f"(v.y), "=f"(v.z), "=f"(v.w) : "r"(a) : "memory"); return v;
}
__device__ __forceinline__ uint4 lds16(uint32_t a) {
  uint4 v; asm volatile("ld.shared.v4.u32 {%0,%1,%2,%3}, [%4];" : "=r"(v.x), "=r"(v.y), "=r"(v.z), "=r"(v.w) : "r"(a) : "memory"); return v;
}
__device__ __forceinline__ uint4 lds16v(uint32_t a) {
  uint4 v; asm volatile("ld.volatile.shared.v4.u32 {%0,%1,%2,%3}, [%4];" : "=r"(v.x), "=r"(v.y), "=r"(v.z), "=r"(v.w) : "r"(a) : "memory"); return v;
}
__device__ __forceinline__ uint32_t lds4v(uint32_t a) { uint32_t v; asm volatile("ld.volatile.shared.u32 %0, [%1];" : "=r"(v) : "r"(a) : "memory"); return v; }
__device__ __forceinline__ float4 lds16fv(uint32_t a) {
  float4 v; asm volatile("ld.volatile.shared.v4.f32 {%0,%1,%2,%3}, [%4];" : "=f"(v.x), "=f"(v.y), "=f"(v.z), "=f"(v.w) : "r"(a) : "memory"); return v;
}
__device__ __forceinline__ uint4 lds16c(uint32_t a) {
  uint4 v; asm volatile("ld.volatile.shared::cluster.v4.u32 {%0,%1,%2,%3}, [%4];" : "=r"(v.x), "=r"(v.y), "=r"(v.z), "=r"(v.w) : "r"(a) : "memory"); return v;
}
__device__ __forceinline__ uint2 lds8v(uint32_t a) {
  uint2 v; asm volatile("ld.volatile.shared.v2.u32 {%0,%1}, [%2];" : "=r"(v.x), "=r"(v.y) : "r"(a) : "memory"); return v;
}
__device__ __forceinline__ uint2 ld_relaxed8(const void* p) {
  uint2 v; asm volatile("ld.relaxed.gpu.global.v2.u32 {%0,%1}, [%2];" : "=r"(v.x), "=r"(v.y) : "l"(p) : "memory"); return v;
}
__device__ __forceinline__ void st_relaxed8(void* p, uint32_t a, uint32_t b) {
  asm volatile("st.relaxed.gpu.global.v2.u32 [%0], {%1,%2};" ::"l"(p), "r"(a), "r"(b) : "memory");
}
__device__ __forceinline__ void st_relaxed16(void* p, uint4 v) {
  asm volatile("st.relaxed.gpu.global.v4.u32 [%0], {%1,%2,%3,%4};" ::"l"(p), "r"(v.x), "r"(v.y), "r"(v.z), "r"(v.w) : "memory");
}
__device__ __forceinline__ void bar_arrive(int id, int n) { asm volatile("bar.arrive %0, %1;" ::"r"(id), "r"(n) : "memory"); }
template <typename T> __device__ __forceinline__ void keep32(T& x) { asm volatile("" : "+r"(x)); }
template <typename T> __device__ __forceinline__ void keep64(T& x) { asm volatile("" : "+l"(x)); }
#define ACC16(d) "+f"(d[0]), "+f"(d[1]), "+f"(d[2]), "+f"(d[3]), "+f"(d[4]), "+f"(d[5]), "+f"(d[6]), "+f"(d[7]), \
                 "+f"(d[8]), "+f"(d[9]), "+f"(d[10]), "+f"(d[11]), "+f"(d[12]), "+f"(d[13]), "+f"(d[14]), "+f"(d[15])
#define OUT16(d) "=f"(d[0]), "=f"(d[1]), "=f"(d[2]), "=f"(d[3]), "=f"(d[4]), "=f"(d[5]), "=f"(d[6]), "=f"(d[7]), \
                 "=f"(d[8]), "=f"(d[9]), "=f"(d[10]), "=f"(d[11]), "=f"(d[12]), "=f"(d[13]), "=f"(d[14]), "=f"(d[15])
template <int ACC> __device__ __forceinline__ void wg_rs32(float* d, const uint32_t* a, uint64_t db) {
  if (ACC == 2)
    asm volatile("wgmma.mma_async.sync.aligned.m64n32k16.f32.bf16.bf16 "
                 "{%0,%1,%2,%3,%4,%5,%6,%7,%8,%9,%10,%11,%12,%13,%14,%15}, {%16,%17,%18,%19}, %20, 0, 1, 1, 0;"
                 : ACC16(d) : "r"(a[0]), "r"(a[1]), "r"(a[2]), "r"(a[3]), "l"(db));
  else if (ACC)
    asm volatile("wgmma.mma_async.sync.aligned.m64n32k16.f32.bf16.bf16 "
                 "{%0,%1,%2,%3,%4,%5,%6,%7,%8,%9,%10,%11,%12,%13,%14,%15}, {%16,%17,%18,%19}, %20, 1, 1, 1, 0;"
                 : ACC16(d) : "r"(a[0]), "r"(a[1]), "r"(a[2]), "r"(a[3]), "l"(db));
  else
    asm volatile("wgmma.mma_async.sync.aligned.m64n32k16.f32.bf16.bf16 "
                 "{%0,%1,%2,%3,%4,%5,%6,%7,%8,%9,%10,%11,%12,%13,%14,%15}, {%16,%17,%18,%19}, %20, 0, 1, 1, 0;"
                 : OUT16(d) : "r"(a[0]), "r"(a[1]), "r"(a[2]), "r"(a[3]), "l"(db));
}
__device__ __forceinline__ void acc_fence16(float* d) { asm volatile("" : ACC16(d)::"memory"); }
__device__ __forceinline__ void wg_ss32(float* d, uint64_t da, uint64_t db) {
  asm volatile("wgmma.mma_async.sync.aligned.m64n32k16.f32.bf16.bf16 "
               "{%0,%1,%2,%3,%4,%5,%6,%7,%8,%9,%10,%11,%12,%13,%14,%15}, %16, %17, 1, 1, 1, 1, 0;"
               : ACC16(d) : "l"(da), "l"(db));
}
__device__ __forceinline__ void wg_ss32z(float* d, uint64_t da, uint64_t db) {
  asm volatile("wgmma.mma_async.sync.aligned.m64n32k16.f32.bf16.bf16 "
               "{%0,%1,%2,%3,%4,%5,%6,%7,%8,%9,%10,%11,%12,%13,%14,%15}, %16, %17, 0, 1, 1, 1, 0;"
               : OUT16(d) : "l"(da), "l"(db));
}

#define STAMP(i)

__device__ __forceinline__ void wgmma_m64n128_ss_tb(float* d, uint64_t da, uint64_t db) {
  asm volatile(
      "wgmma.mma_async.sync.aligned.m64n128k16.f32.bf16.bf16 "
      "{%0,%1,%2,%3,%4,%5,%6,%7,%8,%9,%10,%11,%12,%13,%14,%15,%16,%17,%18,%19,%20,%21,%22,%23,%24,%25,%26,%27,%28,%29,%30,%31,"
      "%32,%33,%34,%35,%36,%37,%38,%39,%40,%41,%42,%43,%44,%45,%46,%47,%48,%49,%50,%51,%52,%53,%54,%55,%56,%57,%58,%59,%60,%61,%62,%63},"
      "%64,%65,1,1,1,0,1;"
      : "+f"(d[0]), "+f"(d[1]), "+f"(d[2]), "+f"(d[3]), "+f"(d[4]), "+f"(d[5]), "+f"(d[6]), "+f"(d[7]), "+f"(d[8]), "+f"(d[9]),
        "+f"(d[10]), "+f"(d[11]), "+f"(d[12]), "+f"(d[13]), "+f"(d[14]), "+f"(d[15]), "+f"(d[16]), "+f"(d[17]), "+f"(d[18]), "+f"(d[19]),
        "+f"(d[20]), "+f"(d[21]), "+f"(d[22]), "+f"(d[23]), "+f"(d[24]), "+f"(d[25]), "+f"(d[26]), "+f"(d[27]), "+f"(d[28]), "+f"(d[29]),
        "+f"(d[30]), "+f"(d[31]), "+f"(d[32]), "+f"(d[33]), "+f"(d[34]), "+f"(d[35]), "+f"(d[36]), "+f"(d[37]), "+f"(d[38]), "+f"(d[39]),
        "+f"(d[40]), "+f"(d[41]), "+f"(d[42]), "+f"(d[43]), "+f"(d[44]), "+f"(d[45]), "+f"(d[46]), "+f"(d[47]), "+f"(d[48]), "+f"(d[49]),
        "+f"(d[50]), "+f"(d[51]), "+f"(d[52]), "+f"(d[53]), "+f"(d[54]), "+f"(d[55]), "+f"(d[56]), "+f"(d[57]), "+f"(d[58]), "+f"(d[59]),
        "+f"(d[60]), "+f"(d[61]), "+f"(d[62]), "+f"(d[63])
      : "l"(da), "l"(db));
}

constexpr int G_STAGES = 4;
constexpr int G_STAGE_BYTES = 32768;
constexpr int G_SMEM = G_STAGES * G_STAGE_BYTES + 128;

__global__ void __launch_bounds__(288, 2)
gemm_kernel(const __grid_constant__ CUtensorMap tmA, const __grid_constant__ CUtensorMap tmB0,
            const __grid_constant__ CUtensorMap tmB1, const __grid_constant__ CUtensorMap tmB2,
            const __grid_constant__ CUtensorMap tmC, int nb_per, int kblocks, int c_col0, const int* done) {
  extern __shared__ __align__(1024) uint8_t smem_raw[];
  const uint32_t sb = smem_u32(smem_raw);
  if (sb & 1023) __trap();
  const uint32_t bars = sb + G_STAGES * G_STAGE_BYTES;
  const int tid = threadIdx.x, wg = tid >> 7;
  asm volatile("griddepcontrol.launch_dependents;" ::: "memory");
  uint32_t rank; asm("mov.u32 %0, %%cluster_ctarank;" : "=r"(rank));
  const int nt = blockIdx.x, mt = blockIdx.y;
  const int bsel = nt / nb_per, n0 = (nt - bsel * nb_per) * 128;
  const CUtensorMap* tb = bsel == 0 ? &tmB0 : (bsel == 1 ? &tmB1 : &tmB2);
  if (tid == 256) {
    for (int i = 0; i < G_STAGES; i++) { mbar_init(bars + i * 8, 1); mbar_init(bars + (G_STAGES + i) * 8, 4); }
    asm volatile("fence.mbarrier_init.release.cluster;" ::: "memory");
    asm volatile("fence.proxy.async;" ::: "memory");
    for (int kb = 0; kb < G_STAGES; kb++) {
      const uint32_t b = sb + kb * G_STAGE_BYTES + 16384, fb = bars + kb * 8;
      mbar_expect_tx(fb, G_STAGE_BYTES);
      tma2d(b, tb, n0, kb * 64, fb);
      tma2d(b + 8192, tb, n0 + 64, kb * 64, fb);
    }
    for (int i = 0; i < (1 << 22); i++) {
      int v; asm volatile("ld.acquire.gpu.global.s32 %0, [%1];" : "=r"(v) : "l"(done) : "memory");
      if (v == 255) break;
    }
    asm volatile("fence.proxy.async;" ::: "memory");
  }
  __syncwarp();
  cluster_sync();
  if (wg == 2) {
    if (tid == 256) {
      STAMP(3);
      for (int kb = 0; kb < kblocks; kb++) {
        const int st = kb % G_STAGES, ph = (kb / G_STAGES) & 1;
        const uint32_t a = sb + st * G_STAGE_BYTES, b = a + 16384, fb = bars + st * 8;
        if (kb >= G_STAGES) { mbar_wait(bars + (G_STAGES + st) * 8, ph ^ 1); mbar_expect_tx(fb, G_STAGE_BYTES); }
        tma2d_mc(a + rank * 8192, &tmA, kb * 64, mt * 128 + rank * 64, fb, (uint16_t)3);
        if (kb >= G_STAGES) { tma2d(b, tb, n0, kb * 64, fb); tma2d(b + 8192, tb, n0 + 64, kb * 64, fb); }
      }
    }
  } else {
    const int cw = wg;
    float acc[64];
#pragma unroll
    for (int i = 0; i < 64; i++) acc[i] = 0.f;
    for (int kb = 0; kb < kblocks; kb++) {
      const int st = kb % G_STAGES, ph = (kb / G_STAGES) & 1;
      mbar_wait(bars + st * 8, ph);
      const uint32_t a = sb + st * G_STAGE_BYTES + cw * 8192, b = sb + st * G_STAGE_BYTES + 16384;
      const uint64_t da = mk_desc(a, 16, 1024), db = mk_desc(b, 8192, 1024);
      WG_FENCE();
#pragma unroll
      for (int k = 0; k < 4; k++) wgmma_m64n128_ss_tb(acc, da + k * 2, db + k * 128);
      WG_COMMIT();
      WG_WAIT(0);
      if (kb + G_STAGES < kblocks && (tid & 127) < 2) mbar_arrive_cluster(mapa(bars + (G_STAGES + st) * 8, tid & 1));
    }
    WG_WAIT(0);
    bar_sync(1, 256);
    const int w4 = (tid >> 5) & 3, lane = tid & 31;
    const uint32_t cbuf = sb + cw * 16384;
    const int row = w4 * 16 + (lane & 7) + ((lane >> 3) & 1) * 8;
#pragma unroll
    for (int j = 0; j < 8; j++) {
      const int chunk = (j & 3) * 2 + (lane >> 4);
      const uint32_t ad = cbuf + (j >> 2) * 8192 + row * 128 + ((chunk ^ (row & 7)) << 4);
      stsm4(ad, pack_bf16(acc[j * 8 + 0], acc[j * 8 + 1]), pack_bf16(acc[j * 8 + 2], acc[j * 8 + 3]),
            pack_bf16(acc[j * 8 + 4], acc[j * 8 + 5]), pack_bf16(acc[j * 8 + 6], acc[j * 8 + 7]));
    }
    asm volatile("fence.proxy.async.shared::cta;" ::: "memory");
    bar_sync(2 + cw, 128);
    if ((tid & 127) == 0) {
      tma2d_store(&tmC, cbuf, c_col0 + nt * 128, mt * 128 + cw * 64);
      tma2d_store(&tmC, cbuf + 8192, c_col0 + nt * 128 + 64, mt * 128 + cw * 64);
      asm volatile("cp.async.bulk.commit_group; cp.async.bulk.wait_group 0;" ::: "memory");
    }
  }
  __syncwarp();
  cluster_sync();
  if (tid == 0) STAMP(4);
  if (nt == 0 && mt == 0) asm volatile("griddepcontrol.wait;" ::: "memory");
}

__host__ __device__ constexpr uint32_t wpage(int L) {
  return (uint32_t)(((L & 1) << 18) | (((L >> 1) & 1) << 20) | (((L >> 2) & 1) << 13) | (((L >> 3) & 1) << 16) | (((L >> 4) & 1) << 17) |
                    (((L >> 5) & 1) << 19) | ((((L >> 2) ^ (L >> 3) ^ (L >> 4) ^ (L >> 5)) & 1) << 12));
}
constexpr int L_MEM = 0;
constexpr int L_U = 4;
constexpr int L_VM = 20;
constexpr int L_FLAG = 52;
constexpr int L_PROBE = 8;
constexpr int VX0 = 32768;
constexpr int EX_K = 4096, EX_CTA = 9216, EX_BYTES = 2 * EX_CTA;
struct Rings {
  uint32_t side[64];
  uint4 ex[4][NH * EX_BYTES / 16];
  int ctr[5][32];
};
__device__ Rings g_rings;
__device__ uint4 g_win[(4 << 20) / 16];
__device__ unsigned g_epoch;
__device__ bf16 g_ux[S_LEN * HD];
constexpr uint32_t TAG = 0x10000u;

constexpr int SB0 = 1024;
#define POLL_LIMIT (1 << 18)

#define TR(i)
#define TRB(i)
#define TRK(t)
#define TRD(c)
#define CNT(i)
#define LOGT(t)
#define ELECT "{.reg .pred p; elect.sync _|p, 0xffffffff; @p "

#define NPRE 2
#define GLA 3
#define CH4 0
#define GFEN 0
#define CHKN 3
#define HN 57
#define H0POS 0
#define LDM lds16v
#define PIN 0
#define H1POS 1
#define QC0 3
#define QC1 9
#define QC2 15
#define QC3 47
#define RESTART 500
#define FIRST 600
#define ALARM 700
#define EXPT 0
#define BACKOFF 200
#define VMPOS 0
#define MEMMC 0
#define CHPOS 1
#define CDEP 1
#define TKN 0
#define NPROBE 4
#define KEEP 1
#define LOOKD 150
#define WPF 0
#define METRO 0
#define BEATS 8
#define P14 7
#define P15 13
#define L14 2
#define L15 8
#define NB 99
#define CL 13
#define CK0 11
#define PINA 0
#define LN 14
#define QUIET 140
#define NEARBY 260
#define ZN 3
#define PACE 2
#define FIX 0
#define XQ 24
#define XS 8
#define BURST 0
#define ATT 1
#define XP 4
template <bool B> struct BoolC { static constexpr bool value = B; };
template <int N> struct IntC { static constexpr int value = N; };
template <typename T> __device__ __forceinline__ T* goff(T* base, uint32_t bytes) {
  return reinterpret_cast<T*>(reinterpret_cast<char*>(base) + bytes);
}
__device__ __forceinline__ char* other(char* p) { return reinterpret_cast<char*>(reinterpret_cast<uintptr_t>(p) ^ 4096); }
__device__ __forceinline__ uint2 ld_tagged8(const void* p) {
  uint2 v;
  asm volatile("{.reg .b64 t; ld.relaxed.gpu.global.b64 t, [%2]; mov.b64 {%0, %1}, t;}" : "=r"(v.x), "=r"(v.y) : "l"(p) : "memory");
  return v;
}
template <int N> __device__ __forceinline__ void landed_all(const uint32_t* w, uint32_t y);
__device__ __forceinline__ uint32_t clk32() { unsigned long long t; asm volatile("mov.u64 %0, %%clock64;" : "=l"(t)::"memory"); return (uint32_t)t; }
__device__ __forceinline__ uint32_t gtime() { unsigned long long t; asm volatile("mov.u64 %0, %%globaltimer;" : "=l"(t)::"memory"); return (uint32_t)t; }
__device__ __forceinline__ uint32_t time_offset(uint32_t z) {
  const uint32_t g0 = gtime() * 9 + z;
  uint32_t a = g0 * -8;
  const uint32_t c0 = clk32();
#pragma unroll
  for (int i = 0; i < 8; i++)
    asm volatile("{.reg .u64 t; .reg .u32 l, h; mov.u64 t, %%globaltimer; mov.b64 {l, h}, t; mad.lo.u32 %0, l, 9, %0;}" : "+r"(a)::"memory");
  return g0 + (a >> 3) - c0 * 5 - (((clk32() - c0) * 5) >> 1);
}
__device__ __forceinline__ void spin_coarse(uint32_t t) {
  asm volatile("{.reg .pred p, q; .reg .u32 i, l, h; .reg .u64 c; .reg .s32 x; mov.u32 i, 0;\n"
               "LC: mov.u64 c, %%globaltimer; mov.b64 {l, h}, c; mad.lo.s32 x, l, 9, %0; add.u32 i, i, 1; setp.lt.u32 q, i, 4096;\n"
               "setp.lt.and.s32 p, x, 0, q; @p bra LC;}" ::"r"(-t) : "memory");
}
__device__ __forceinline__ void spin_until(uint32_t t, uint32_t tk) {
  const uint32_t d = tk - t;
  asm volatile("{.reg .pred p, q; .reg .u32 i, l, h; .reg .u64 c; .reg .s32 x; mov.u32 i, 0;\n"
               "LS: mov.u64 c, %%clock64; mov.b64 {l, h}, c; mad.lo.s32 x, l, 5, %0; add.u32 i, i, 1; setp.lt.u32 q, i, 4096;\n"
               "setp.lt.and.s32 p, x, 0, q; @p bra LS;}" ::"r"(d) : "memory");
}
__device__ __forceinline__ uint32_t approach(uint32_t t, uint32_t z) { spin_coarse(t - NEARBY * 5); return time_offset(z); }
struct Pace { int f0, u0, m0, mu, mm, ok, late, dec, cap, s, c; };
__device__ __forceinline__ uint2 last_stores(uint4 f, const char* flags, int s) {
  for (int it = 0; __any_sync(~0u, ((f.x ^ s) | (f.y ^ s) | (f.z ^ s) | (f.w ^ s)) & 31); it++) {
    CNT(4);
    if (it) spin_until(clk32() * 5 + BACKOFF * 5, 0);
    f = ld_relaxed16(flags);
    if (it > POLL_LIMIT) FAIL(7000 + s);
  }
  const uint32_t now = gtime() * 9 + 65536;
  return make_uint2(now - __reduce_min_sync(~0u, min(now - f.x, now - f.y)), now - __reduce_min_sync(~0u, min(now - f.z, now - f.w)));
}
__device__ __forceinline__ int track(int e, int x, const Pace& d) { return max(min(x, e + d.cap), e - max(max(d.dec, (e - x) >> 2), e - x - d.cap)); }
__device__ __forceinline__ uint4 next_plan(uint4 p, uint2 l, int s, const Pace& d) {
  const bool late = (int)(l.x + d.ok - p.y) > 0 || s == 0;
  int eu = p.z, em = p.w & ~1;
  if (s && (int)(l.y + d.ok - p.x) <= 0) eu = track(eu, l.x - p.x, d);
  if (p.w & 1) em = track(em, l.y - p.x + em + d.mm, d) & ~1;
  const uint32_t tm = (late ? l.x + (s ? d.late : d.f0) : p.y) + em + d.mm;
  return make_uint4(tm, tm + eu + d.mu, eu, em | !late);
}
__device__ __forceinline__ const char* flag_ptr(const char* G, uint32_t near, uint32_t t16, int s) {
  keep32(t16);
  return reinterpret_cast<const char*>(reinterpret_cast<uintptr_t>(G + ((wpage(L_FLAG) ^ near) + (s & 1) * 512)) | (t16 & 0x1F0));
}
__device__ __forceinline__ void arrive_all(uint32_t CS, uint32_t t16, uint32_t off) {
  keep32(t16);
  const uint32_t l = (t16 >> 4) & 31;
  if (l < CS) mbar_arrive_cluster(mapa(SB0 + off, l));
  __syncwarp();
}
template <int N> __device__ __forceinline__ uint32_t idle(uint32_t z) {
#pragma unroll
  for (int i = 0; i < N; i++) asm volatile("mad.lo.u32 %0, %0, %0, %0;" : "+r"(z));
  return z;
}
__device__ __forceinline__ uint32_t junk() { uint32_t x; asm volatile("" : "=r"(x)); return x; }
__device__ __forceinline__ float rcp_fast(float x) { float y; asm("rcp.approx.ftz.f32 %0, %1;" : "=f"(y) : "f"(x)); return y; }
__device__ __forceinline__ void mma_z(float* d, uint32_t a0, uint32_t a1, uint32_t a2, uint32_t a3, uint32_t b0, uint32_t b1) {
  asm volatile("mma.sync.aligned.m16n8k16.row.col.f32.bf16.bf16.f32 {%0,%1,%2,%3}, {%4,%5,%6,%7}, {%8,%9}, {%10,%10,%10,%10};"
               : "=f"(d[0]), "=f"(d[1]), "=f"(d[2]), "=f"(d[3])
               : "r"(a0), "r"(a1), "r"(a2), "r"(a3), "r"(b0), "r"(b1), "f"(0.f));
}
__device__ __forceinline__ void mma1688z(float* d, uint32_t a0, uint32_t a1, uint32_t b0) {
  asm volatile("mma.sync.aligned.m16n8k8.row.col.f32.bf16.bf16.f32 {%0,%1,%2,%3}, {%4,%5}, {%6}, {%7,%7,%7,%7};"
               : "=f"(d[0]), "=f"(d[1]), "=f"(d[2]), "=f"(d[3]) : "r"(a0), "r"(a1), "r"(b0), "f"(0.f));
}
#define MMA_W(d, o, b0, b1) mma16816(d, w[o], w[(o) + 1], w[(o) + 2], w[(o) + 3], b0, b1)
#define MMA_X(d, x, b0, b1) mma16816(d, (x)[0], (x)[1], (x)[2], (x)[3], b0, b1)
#define MMA_XZ(d, x, b0, b1) mma_z(d, (x)[0], (x)[1], (x)[2], (x)[3], b0, b1)
__device__ __forceinline__ void ldw(uint32_t* x, uint32_t a) { ldsm4t(x[0], x[1], x[2], x[3], a); }
__device__ __forceinline__ void ldm(uint32_t* x, uint32_t a) { ldsm4(x[0], x[1], x[2], x[3], a); }
__device__ __forceinline__ void ldm_if(uint32_t* x, uint32_t a, uint32_t c) {
  asm volatile("{.reg .pred p; setp.ne.u32 p, %5, 0; @p ldmatrix.sync.aligned.m8n8.x4.shared.b16 {%0,%1,%2,%3}, [%4];}"
               : "=r"(x[0]), "=r"(x[1]), "=r"(x[2]), "=r"(x[3]) : "r"(a), "r"(c) : "memory");
}
__device__ __forceinline__ void bulk(uint32_t dst, const void* src, uint32_t n, uint32_t bar) {
  asm volatile(ELECT "cp.async.bulk.shared::cluster.global.mbarrier::complete_tx::bytes [%0], [%1], %2, [%3];}" ::"r"(dst), "l"(src), "r"(n), "r"(bar) : "memory");
}
template <uint32_t MASK> __device__ __forceinline__ void bulk_mc(uint32_t dst, const void* src, uint32_t n, uint32_t bar) {
  asm volatile(ELECT "cp.async.bulk.shared::cluster.global.mbarrier::complete_tx::bytes.multicast::cluster [%0], [%1], %2, [%3], %4;}"
               ::"r"(dst), "l"(src), "r"(n), "r"(bar), "h"((uint16_t)MASK) : "memory");
}
__device__ __forceinline__ void issue_x(const CUtensorMap* tm, uint32_t dst, uint32_t bar, int seg, int chunk, uint32_t mask) {
  asm volatile(ELECT "cp.async.bulk.tensor.3d.shared::cluster.global.mbarrier::complete_tx::bytes.multicast::cluster [%0], [%1, {%3, %4, %5}], [%2], %6;}"
               ::"r"(dst), "l"(tm), "r"(bar), "r"(0), "r"(seg * SEG), "r"(chunk), "h"((uint16_t)mask) : "memory");
}
__device__ __forceinline__ void expect(uint32_t bar, uint32_t bytes) {
  asm volatile(ELECT "mbarrier.arrive.expect_tx.shared::cta.b64 _, [%0], %1;}" ::"r"(bar), "r"(bytes) : "memory");
}
__device__ __forceinline__ void wait_ft(uint32_t bar, uint32_t par) {
  asm volatile("{.reg .pred p, q; .reg .u32 i; mov.u32 i, 0;\n"
               "LW: add.u32 i, i, 1; setp.lt.u32 q, i, 0x20000;\n"
               "mbarrier.try_wait.parity.shared::cta.b64 p, [%0], %1;\n"
               "not.pred p, p; and.pred q, q, p; @q bra LW;}" ::"r"(bar), "r"(par) : "memory");
}
__device__ __forceinline__ char* ptr64(uint32_t lo, uint32_t hi) { return reinterpret_cast<char*>(((uint64_t)hi << 32) | lo); }
__device__ __forceinline__ uint32_t plo(const void* p) { return (uint32_t)reinterpret_cast<uintptr_t>(p); }
__device__ __forceinline__ uint32_t phi(const void* p) { return (uint32_t)(reinterpret_cast<uintptr_t>(p) >> 32); }
__device__ __forceinline__ uint32_t pack_tag(float lo, float hi, uint32_t tg) {
  return ((__float_as_uint(hi) + (tg ^ TAG)) & 0xFFFE0000u) | pack_bf16(lo, __uint_as_float(tg));
}
__device__ __forceinline__ void st_tagged8(void* p, uint32_t a, uint32_t b) {
  asm volatile("{.reg .b64 t; mov.b64 t, {%1, %2}; st.relaxed.gpu.global.b64 [%0], t;}" ::"l"(p), "r"(a), "r"(b) : "memory");
}
__device__ __forceinline__ void st_tagged8_if(void* p, uint32_t a, uint32_t b, bool c) {
  asm volatile("{.reg .b64 t; .reg .pred q; setp.ne.u32 q, %3, 0; mov.b64 t, {%1, %2}; @q st.relaxed.gpu.global.b64 [%0], t;}" ::"l"(p), "r"(a), "r"(b), "r"((uint32_t)c) : "memory");
}
__device__ __forceinline__ void st_tagged16(void* p, uint4 v) {
  asm volatile("{.reg .b128 t; .reg .b64 a, b; mov.b64 a, {%1, %2}; mov.b64 b, {%3, %4}; mov.b128 t, {a, b}; st.relaxed.gpu.global.b128 [%0], t;}"
               ::"l"(p), "r"(v.x), "r"(v.y), "r"(v.z), "r"(v.w) : "memory");
}
__device__ __forceinline__ uint4 ld_tagged16(const void* p) {
  uint4 v;
  asm volatile("{.reg .b128 t; .reg .b64 a, b; ld.relaxed.gpu.global.b128 t, [%4]; mov.b128 {a, b}, t; mov.b64 {%0, %1}, a; mov.b64 {%2, %3}, b;}"
               : "=r"(v.x), "=r"(v.y), "=r"(v.z), "=r"(v.w) : "l"(p) : "memory");
  return v;
}
__device__ __forceinline__ void chk2(uint32_t& c, const uint4& v, uint32_t tg) {
  asm volatile("lop3.b32 %0, %0, %1, %3, 0xF6; lop3.b32 %0, %0, %2, %3, 0xF6;" : "+r"(c) : "r"(v.x), "r"(v.z), "r"(tg));
}
__device__ __forceinline__ void sched_fence(uint32_t zero, int n) {
  asm volatile("{.reg .pred p; setp.eq.u32 p, %0, %1; @p exit;}" ::"r"(zero), "r"(n + 1001) : "memory");
}
#define HERE(x) x |= clk32() & zero
__device__ __forceinline__ void pin(uint64_t& x, uint32_t zero) {
  asm volatile("{.reg .pred p; setp.ne.u32 p, %1, 0; @p mov.u64 %0, %%clock64;}" : "+l"(x) : "r"(zero) : "memory");
}
__device__ __forceinline__ void landed(uint32_t y) {
  asm volatile("{.reg .pred p; setp.ne.u32 p, %0, 0; vote.sync.any.pred p, p, 0xffffffff; @p exit;}" ::"r"(y) : "memory");
}
template <int N> __device__ __forceinline__ void landed_all(const uint32_t* w, uint32_t y) {
#pragma unroll
  for (int i = 0; i < N; i += 4) y &= w[i];
  landed(y);
}
__device__ __forceinline__ uint64_t cdesc(uint32_t v, int off) {
  const uint32_t lo = v + (uint32_t)(((SB0 + off) >> 4) | (1 << 16));
  return ((uint64_t)0x40000040u << 32) | lo;
}
__device__ __forceinline__ uint64_t ndesc(uint32_t v, int off, int kstr, int mstr) {
  const uint32_t lo = v + (uint32_t)(((SB0 + off) >> 4) | ((kstr >> 4) << 16));
  return ((uint64_t)(mstr >> 4) << 32) | lo;
}
__device__ __forceinline__ constexpr int xk(int k) { return (k >> 2) * 4096 + (k & 3) * 32; }
constexpr uint32_t ONE2 = 0x3F803F80u;
constexpr float SCL = 0.08838834764831845f * 1.4426950408889634f;
__device__ __forceinline__ void exp10v(float* sc) {
  float ml = fmaxf(fmaxf(fmaxf(sc[0], sc[1]), fmaxf(sc[2], sc[3])), fmaxf(fmaxf(sc[4], sc[5]), fmaxf(sc[6], sc[7])));
  ml = fmaxf(ml, fmaxf(sc[8], sc[9]));
  const float m1 = __shfl_xor_sync(~0u, ml, 1), m2 = __shfl_xor_sync(~0u, ml, 2), m3 = __shfl_xor_sync(~0u, ml, 3);
  const float mo = fmaxf(fmaxf(ml, m1), fmaxf(m2, m3));
#pragma unroll
  for (int i = 0; i < 10; i++) sc[i] = ex2(sc[i] - mo);
}
#define UNI(x) __reduce_max_sync(~0u, (uint32_t)(x))
#define OPQ(x) __shfl_sync(~0u, (uint32_t)(x), lane)
#define BASES() uint32_t t16 = t16_; keep32(t16); const uint32_t l16 = t16 + wofs; (void)l16
__device__ __forceinline__ void probe_init(char* G, int id) {
  const int t = threadIdx.x;
  if (t < 32) *reinterpret_cast<uint4*>(G + ((wpage(L_PROBE + (id >> 5)) ^ ((t & 2) << 11)) + 16384 + ((id + (t >> 2)) & 31) * 128 + (t & 1) * 16)) = make_uint4(0, 0, 0, 0);
}
__device__ __forceinline__ void probe_near(char* G, int id, uint32_t dst) {
  unsigned* p0 = reinterpret_cast<unsigned*>(G + wpage(L_PROBE + (id >> 5)) + 16384 + (id & 31) * 128);
  unsigned best[2] = {~0u, ~0u};
#pragma unroll 2
  for (int i = 0; i < NPROBE; i++) {
    const unsigned t0 = clk32();
    const unsigned x = atomicExch(reinterpret_cast<unsigned*>(reinterpret_cast<uintptr_t>(p0) ^ ((i & 1) << 12)), (unsigned)i);
    asm volatile("{.reg .pred p; setp.eq.u32 p, %0, 0xffffffff; @p exit;}" ::"r"(x) : "memory");
    best[i & 1] = min(best[i & 1], clk32() - t0);
  }
  asm volatile("red.shared.min.u32 [%0], %1; red.shared.min.u32 [%0 + 4], %2;" ::"r"(dst), "r"(best[0]), "r"(best[1]) : "memory");
}
__device__ __forceinline__ uint32_t pick_near(uint32_t CS, uint32_t off) {
  uint32_t a, b;
  asm volatile("ld.shared::cluster.v2.u32 {%0, %1}, [%2];" : "=r"(a), "=r"(b) : "r"(mapa(SB0 + off, threadIdx.x & (CS - 1))) : "memory");
  return UNI(__reduce_min_sync(~0u, b) < __reduce_min_sync(~0u, a) ? 4096u : 0u);
}
__device__ __forceinline__ void start_arrive(uint32_t dst) {
  asm volatile("fence.proxy.async.global;" ::: "memory");
  __threadfence();
  sts4f(dst, __uint_as_float((atomicAdd(&g_epoch, 1u) & ~127u) + 128u));
}
__device__ __forceinline__ void start_wait(uint32_t src) {
  const unsigned target = lds4(src);
  for (int i = 0;; i++) {
    unsigned v; asm volatile("ld.acquire.gpu.global.u32 %0, [%1];" : "=r"(v) : "l"(&g_epoch) : "memory");
    if (__all_sync(~0u, (int)(v - target) >= 0) || i > (1 << 20)) break;
  }
}

template <int CS> __device__ __forceinline__ void fetch_mem_mc(uint32_t dst, const char* G, uint32_t off, int rank, uint32_t bar) {
  constexpr int PB = CS == 8 ? 2048 : 4096;
#pragma unroll
  for (int i = 0; i < 16384 / PB / CS; i++) {
    const uint32_t o = (rank * (16384 / PB / CS) + i) * PB;
    bulk_mc<(1u << CS) - 1>(dst + o, G + (off + ((o & 4096) << 6) + ((o & 8192) << 7) + (o & 4095)), PB, bar);
  }
}
template <int wg, int MEM, bool PRE, typename GV, typename W, typename F>
__device__ __forceinline__ void gemv_mem(GV& gv, const uint32_t* w, int s, uint32_t t16_, uint32_t wofs, uint32_t near, char* G, W wsa,
                                         uint32_t bar, uint32_t zero, uint32_t trc, F hook) {
  const uint32_t tg = (s & 1) << 16;
#pragma unroll 1
  for (;;) {
    BASES();
    const uint32_t mb = l16 + MEM + wg * 8192;
    if (PRE) landed(gv.prefetch(lds4(wsa(t16))) & zero);
    TR(14);
    wait_ft(bar, s & 1);
    TR(0);
    gv.first(mb);
    gv.c = 0;
    gv.tg = tg; gv.z0 = zero;
    bool bad;
    gv.template run<0, 16>(w, mb, [&](auto nc) __attribute__((always_inline)) {
      if (decltype(nc)::value == GV::CV) bad = __any_sync(~0u, gv.c & (s ? TAG : 0));
      hook(nc, bad);
    });
    if (__builtin_expect(!bad, 1)) break;
    CNT(MEM == 0x28000 ? 0 : 2);
    uint4 v[4];
    const char* src = G + (near + (wg << 20) + ((t16 - SB0) & 0x7F0));
    for (int it = 0;; it++) {
      uint32_t c = 0;
#pragma unroll
      for (int i = 0; i < 4; i++) v[i] = ld_tagged16(src + (i & 1) * 2048 + (i >> 1) * (1 << 18));
#pragma unroll
      for (int i = 0; i < 4; i++) chk2(c, v[i], tg);
      if (!__any_sync(~0u, c & TAG)) break;
      if (it > POLL_LIMIT) FAIL(2000);
    }
    bar_sync(1 + wg, 128);
#pragma unroll
    for (int i = 0; i < 4; i++) sts16(t16 + (MEM + wg * 6144) + i * 2048, v[i]);
    if (!PRE) landed(gv.prefetch(lds4(wsa(t16))) & zero);
    bar_sync(1 + wg, 128);
  }
}

constexpr int A_WS = 0;
constexpr int A_X = 65536;
constexpr int A_H1 = A_X + 32768;
constexpr int A_MEM = A_X + 98304;
constexpr int A_QX = A_MEM + 16384, A_KX = A_QX + EX_K, A_QM = A_QX + EX_CTA;
constexpr int A_KM = A_QM + 2048;
constexpr int A_SB = A_KM + 2048;
constexpr int A_BARS = A_X + 131072;
constexpr int A_TRC = A_BARS + 256;
constexpr int A_TAB = A_BARS + 1024;
constexpr int A_PQ = A_TAB + 16384;
constexpr int A_SMEM = A_PQ + 8192;
constexpr int B_RES = 64, B_PAIR = 72, B_H0 = 80, B_H1 = 88  , B_M = 104, B_XE = 112, B_EXD = 120, B_HO = 0  , B_T = 128  , B_NEAR = 160, B_EP = 168, B_TK = 176, B_CHK = 184;

template <int NP> struct GemvQK {
  float a[4], b[4], a2[4], b2[4];
  uint4 m[16];
  uint32_t pp[4][16], ws;
  static __device__ __forceinline__ constexpr int blk(int n) {
    return NP == 2 ? (n < 2 ? 12 + n : n == P14 ? 14 : n == P15 ? 15 : n - 2 - (n > P14) - (n > P15)) : (n < 3 ? 12 + n : n == 10 ? 15 : n - 3 - (n > 10));
  }
  static __device__ __forceinline__ constexpr int lm(int n) { return NP == 3 && n < 1 ? n + 3 : NP == 3 && n < 2 ? n + 4 : n + 1 + GLA > 16 ? 16 : n + 1 + GLA; }
  static __device__ __forceinline__ constexpr int lw(int n) {
    return NP == 2 ? (n >= L14 && n < L14 + 4 ? 8 + n - L14 : n >= L15 && n < L15 + 4 ? 12 + n - L15 : 0)
                   : (n >= 3 && n <= 8 && n != 5 && n != 7 ? 9 + n - (n > 5) - (n > 7) : 0);
  }
  template <int J0 = 0, int J1 = NP * 4> __device__ __forceinline__ uint32_t prefetch(uint32_t a) {
    ws = a;
    uint32_t y = ~0u;
#pragma unroll
    for (int j = J0; j < J1; j++) { ldw(pp[j >> 2] + (j & 3) * 4, ws + (j >> 1) * 2048 + (j & 1) * 16384); y &= pp[j >> 2][(j & 3) * 4]; }
    return y;
  }
  template <int N, typename F> __device__ __forceinline__ void run(const uint32_t* w, uint32_t mb, F hook) {
    if constexpr (N < 16) {
      if (N == 0) {
#pragma unroll
        for (int n = 0; n < lm(-1); n++) m[n] = lds16v(mb + blk(n) * 512);
      }
      constexpr int bi = blk(N), o2 = bi >= 12 ? 8 : 4, j = lw(N);
      const uint32_t* pa = bi >= 12 ? pp[bi >= 12 ? bi - 12 : 0] : w + bi * 8;
      const uint32_t* pb = bi >= 12 ? pa + 4 : pa + 96;
      if (N == 0) { MMA_XZ(a, pa, m[N].x, m[N].y); MMA_XZ(b, pb, m[N].x, m[N].y); MMA_XZ(a2, pa + o2, m[N].z, m[N].w); MMA_XZ(b2, pb + o2, m[N].z, m[N].w); }
      else { MMA_X(a, pa, m[N].x, m[N].y); MMA_X(b, pb, m[N].x, m[N].y); MMA_X(a2, pa + o2, m[N].z, m[N].w); MMA_X(b2, pb + o2, m[N].z, m[N].w); }
#pragma unroll
      for (int n = lm(N - 1); n < lm(N); n++) m[n] = lds16v(mb + blk(n) * 512);
      if (j) ldw(pp[j >> 2] + (j & 3) * 4, ws + (j >> 1) * 2048 + (j & 1) * 16384);
      hook(IntC<N>());
      run<N + 1>(w, mb, hook);
    }
  }
  __device__ __forceinline__ void store(uint32_t ad) {
    stsm4t(ad, pack_bf16(a[0] + a2[0], a[1] + a2[1]), pack_bf16(a[2] + a2[2], a[3] + a2[3]), pack_bf16(b[0] + b2[0], b[1] + b2[1]), pack_bf16(b[2] + b2[2], b[3] + b2[3]));
  }
};

#define TKA (bars + B_TK)
__device__ __forceinline__ void qk_body(const CUtensorMap& tmWq, const CUtensorMap& tmWk, const CUtensorMap& tmX,
                                        char* __restrict__ G, const Pace d, int zero, int block, const int CS) {
  extern __shared__ __align__(1024) uint8_t smem_raw[];
  const uint32_t sb = smem_u32(smem_raw);
  if ((sb & 0x3FFFF) != SB0) __trap();
  if (block != 63) asm volatile("griddepcontrol.launch_dependents;" ::: "memory");
  const int tid = threadIdx.x, t7 = tid & 127, lane = tid & 31;
  const int warp = UNI(tid >> 5), wg = warp >> 2, w4 = warp & 3;
  const uint32_t wofs = UNI((tid >> 5) * -512);
  const int cta = UNI(block), r = cta & 1, head = cta >> 1, fcol = cta * 64, rank = cta & (CS - 1);
  const uint32_t bars = sb + A_BARS;
  const uint32_t trc = UNI(sb + A_TRC + (tid >> 5) * 64); (void)trc;
  if (tid == 0) {
    STAMP(CS > 2 ? 8 : 11);
    for (int i = 0; i < 9; i++) mbar_init(bars + i * 8, 1);
    asm volatile("fence.mbarrier_init.release.cluster;" ::: "memory");
#pragma unroll 1
    for (int i = 0; i < 12; i++) {
      const int t = i >> 1, h = i & 1;
      const uint32_t b = bars + h * 32 + (t >> 1) * 8;
      if (!(t & 1)) mbar_expect_tx(b, 32768);
      tma2d_ef(sb + (t < 2 ? A_WS + h * 32768 : A_X + h * 65536 - 32768) + t * 16384, t < 3 ? &tmWk : &tmWq, fcol, h * 512 + (t % 3) * 128, b);
    }
    for (int i = 9; i < 32; i++) if ((i & 24) != 16) mbar_init(bars + i * 8, i * 8 == B_XE ? CS : 1);
    asm volatile("fence.mbarrier_init.release.cluster;" ::: "memory");
    mbar_expect_tx(bars + B_RES, 65536);
    sts8f(bars + B_NEAR, __uint_as_float(~0u), __uint_as_float(~0u));
  }
  if (cta == 63 && tid < 32) reinterpret_cast<int4*>(g_rings.ctr)[tid] = make_int4(-1, -1, -1, -1);
  const uint32_t gu = wpage(L_U + (cta >> 2)) + (cta & 3) * 1024;
  if (tid < 128) *reinterpret_cast<uint4*>(G + ((gu + (tid & 63) * 16) ^ ((tid & 64) << 6))) = make_uint4(0, 0, 0, 0);
  probe_init(G, cta * 8);
  if (tid < 4) *reinterpret_cast<uint32_t*>(G + (wpage(L_FLAG) ^ ((tid & 1) << 12)) + (tid >> 1) * 512 + head * 16 + r * 4) = 30;
  __syncthreads();
  const int lk = (lane & 7) + ((lane >> 4) << 3);
  const uint32_t wt_off = lk * 128 + (((((tid >> 4) & 6) + ((lane >> 3) & 1)) ^ (lk & 7)) << 4);
  const int g = lane >> 2, c = lane & 3;
  uint32_t w[192];
  const uint32_t t16_ = OPQ(sb + tid * 16);
#pragma unroll
  for (int i = 0; i < 6; i++) {
    if (!(i & 1)) mbar_wait(bars + wg * 32 + (i >> 1) * 8, 0);
    const uint32_t a = sb + (i < 2 ? A_WS + wg * 32768 : A_X + wg * 65536 - 32768) + i * 16384 + wt_off;
#pragma unroll
    for (int j = 0; j < 8; j++) ldw(w + (i * 8 + j) * 4, a + j * 2048);
    if (i == 1) {
      landed_all<64>(w, zero);
      bar_sync(1 + wg, 128);
      if (t7 == 0)
        for (int m = 0; m < 2; m++) tma2d_ef(sb + A_WS + wg * 32768 + m * 16384, m ? &tmWq : &tmWk, fcol, wg * 512 + 384, bars + B_RES);
      if (lane == 0) probe_near(G, cta * 8 + (tid >> 5), bars + B_NEAR);
      __syncwarp();
    }
  }
  landed_all<128>(w + 64, zero);
  cluster_sync_relaxed();
  if (tid == 0) STAMP(CS > 2 ? 9 : 12);
  const uint32_t near = pick_near(CS, A_BARS + B_NEAR);
  auto fetch_x = [&](uint32_t buf, uint32_t bar, int n, int h) __attribute__((always_inline)) {
    if (CS == 8) issue_x(&tmX, sb + buf + rank * 4096, bars + bar, n, h * 8 + rank, 255);
    else issue_x(&tmX, sb + buf + rank * 16384, bars + bar, n, h * 8 + rank * 4, 3);
  };
  if (warp == 7) {
    expect(bars + B_H0, 32768); expect(bars + B_H1, 32768); expect(bars + B_H1 + 8, 32768);
    fetch_x(A_H1, B_H1, 0, 1); fetch_x(A_X, B_H0, 0, 0); fetch_x(A_H1 + 32768, B_H1 + 8, 1, 1);
    expect(bars + B_PAIR, 1536);
    expect(bars + B_M, 16384);
  }
  const uint32_t rdelta = UNI(mapa(sb, rank ^ 1) - sb);
  {
    const int w4 = (tid >> 5) & 3, wg = tid >> 7;
    const int ch = 2 * w4 + ((lane >> 3) & 1);
    const uint32_t qst = sb + (lane & 7) * 16 + ((lane >> 4) ? A_QM + ch * 256 + wg * 128 : A_KM + wg * 1024 + ch * 128);
    const uint32_t fst = sb + (lane & 7) * 16 + (wg ? A_QX + w4 * 1024 + (lane >> 3) * 128 : A_KX + ch * 640 + (lane >> 4) * 128);
    const uint32_t kba = sb + (wg && w4 < 2 ? A_KM + w4 * 1024 + lane * 16 : (lane & 7) * 16 + A_KX + (lane >> 3) * 640 + (wg ? 4 : w4) * 128);
    const char* vmp = G + ((wpage(L_VM + head) ^ near) + r * 2048 + t7 * 8);
    const char* up = G + ((gu ^ near ^ 4096) + (w4 >> 1) * 512 + g * 64 + (w4 & 1) * 32 + c * 8);
    const char* vxp = G + ((wpage(cta) ^ near) + VX0 + w4 * 1024 + lane * 16);
    sts16(t16_ + A_TAB, make_uint4(sb + A_MEM + tid * 32 + ((lane >> 2) & 3) * 8, qst, kba, sb + A_SB + lane * 16 + (w4 & 1) * 8 + min(tid >> 6, 2) * 512));
    sts16(t16_ + A_TAB + 4096, make_uint4(plo(vmp), phi(vmp), plo(vxp), phi(vxp)));
    sts16(t16_ + A_TAB + 8192, make_uint4(sb + rdelta + A_SB + 1536 + tid * 8, bars + B_PAIR + rdelta, fst, sb + A_WS + wg * 32768 + wt_off));
    sts16(t16_ + A_TAB + 12288, make_uint4(plo(up), phi(up), plo(up) ^ 4096, phi(up)));
    if (tid == 0) { const uint32_t t = gtime() * 9; sts16(bars + B_T, make_uint4(t, t, d.u0, d.m0)); sts4f(bars + B_T + 16, __uint_as_float(t - 1)); sts4f(bars + B_CHK, 0.f); }
    if (tid == 32) {
      start_arrive(bars + B_EP);
      asm volatile("griddepcontrol.launch_dependents;" ::: "memory");
      st_relaxed4(&g_rings.side[cta], lds4(bars + B_EP) + (near >> 12));
    }
  }
  __syncthreads();
  auto fetch_mem = [&](uint32_t slot, auto wait) __attribute__((always_inline)) {
    if (CS == 8) { wait(); fetch_mem_mc<8>(sb + A_MEM, G, near + slot, rank, bars + B_M); }
    else {
      wait();
#pragma unroll
      for (int p = 0; p < 4; p++) bulk(sb + A_MEM + p * 4096, G + (near + slot) + wpage(L_MEM + p), 4096, bars + B_M);
    }
  };
  const uint32_t hob = UNI(sb + A_BARS + 192 + ((tid >> 2) & 24));
  auto proj = [&](int s, auto& gv, auto wg_c, auto gate, auto mid, auto between, auto mid2, auto mid3) __attribute__((always_inline)) {
    constexpr int wg = decltype(wg_c)::value, XB = wg ? A_H1 : A_X;
    uint32_t z = wg ? ((s + 1) & 1) * 2048 : s & wofs & zero;
    float d[16];
    uint32_t f[8];
    auto pass = [&](auto m_c, auto first_c) __attribute__((always_inline)) {
      constexpr int m = decltype(m_c)::value;
      constexpr bool first = decltype(first_c)::value;
      if (first) {
        const uint32_t ws = lds4v(t16_ + A_TAB + 8204);
        gate([&](uint32_t z) __attribute__((always_inline)) { gv.template prefetch<0, 4>(ws | z); });
      }
      WG_FENCE();
#pragma unroll
      for (int k = 0; k < XQ; k++) {
        if (k == 0) wg_rs32<0>(d, w + m * 96, cdesc(z, XB)); else wg_rs32<1>(d, w + m * 96 + 4 * k, cdesc(wg || k < ZN ? z : 0, XB + xk(k)));
      }
#pragma unroll
      for (int j = 2; j < XS; j++) wg_ss32(d, cdesc(0, A_WS + wg * 32768 + m * 16384 + j * 2048), cdesc(wg ? z : 0, XB + xk(24 + j)));
#pragma unroll
      for (int j = 0; j < 2; j++) wg_rs32<1>(d, gv.pp[0] + j * 8 + m * 4, cdesc(wg ? z : 0, XB + xk(24 + j)));
      WG_COMMIT();
    };
    pass(IntC<1 - wg>(), BoolC<true>());
    TR(8);
    mid();
    z = wg ? UNI(z | zero) : 0;
    WG_WAIT(0);
    TR(9);
    acc_fence16(d);
    sts16(t16_ + A_PQ, make_uint4(pack_bf16(d[0], d[1]), pack_bf16(d[2], d[3]), pack_bf16(d[4], d[5]), pack_bf16(d[6], d[7])));
    sts16(t16_ + A_PQ + 4096, make_uint4(pack_bf16(d[8], d[9]), pack_bf16(d[10], d[11]), pack_bf16(d[12], d[13]), pack_bf16(d[14], d[15])));
    __syncwarp();
    asm volatile(ELECT "mbarrier.arrive.shared::cta.b64 _, [%0];}" ::"r"(hob + wg * 32) : "memory");
    between();
    pass(IntC<wg>(), BoolC<false>());
    mid2();
    wait_ft(hob + 32 - wg * 32, (s + 1) & 1);
    const uint4 p0 = lds16v(t16_ + A_PQ + 2048 - wg * 4096), p1 = lds16v(t16_ + A_PQ + 6144 - wg * 4096);
    const uint2 tc = lds8v(t16_ + A_TAB + 8200);
    if (ATT) wait_ft(bars + B_EXD, s & 1);
    mid3();
    TR(10);
    WG_WAIT(0);
    TR(11);
    acc_fence16(d);
    const uint32_t p[8] = {p0.x, p0.y, p0.z, p0.w, p1.x, p1.y, p1.z, p1.w};
#pragma unroll
    for (int i = 0; i < 8; i++) f[i] = pack_bf16(d[2 * i] + __uint_as_float(p[i] << 16), d[2 * i + 1] + __uint_as_float(p[i] & 0xFFFF0000u));
    stsm4t(tc.x, f[0], f[1], f[2], f[3]); stsm4t(tc.x + (wg ? 512 : 256), f[4], f[5], f[6], f[7]);
    gv.template prefetch<4>(tc.y);
    if (wg == 0) bar_sync(1, 128);
  };
  auto fetch_h1 = [&](int s, int w4) __attribute__((always_inline)) {
    if (w4 == 1 && s + 2 < NSEG) {
      expect(bars + B_H1 + (s & 1) * 8, 32768);
      fetch_x(A_H1 + (s & 1) * 32768, B_H1 + (s & 1) * 8, s + 2, 1);
    }
  };
  auto send_qk = [&](int s) __attribute__((always_inline)) {
    asm volatile(ELECT "cp.async.bulk.global.shared::cta.bulk_group [%0], [%1], %2;}"
                 ::"l"(reinterpret_cast<char*>(g_rings.ex[s & 3]) + cta * EX_CTA), "r"(sb + A_QX), "r"(EX_CTA) : "memory");
    asm volatile("cp.async.bulk.commit_group;" ::: "memory");
  };
  auto sent_qk = [&]() __attribute__((always_inline)) {
    asm volatile("cp.async.bulk.wait_group 0;" ::: "memory");
    __syncwarp();
    asm volatile(ELECT "mbarrier.arrive.shared::cta.b64 _, [%0];}" ::"r"(bars + B_EXD) : "memory");
  };
  auto sum_km = [&]() __attribute__((always_inline)) {
    BASES();
    const uint32_t ka = lds4(t16 + A_TAB + 8);
    uint32_t kb[16];
#pragma unroll
    for (int i = 0; i < 4; i++) ldm(kb + 4 * i, l16 + A_KM + i * 512);
#pragma unroll
    for (int i = 0; i < 8; i++) asm("add.rn.bf16x2 %0, %0, %1;" : "+r"(kb[i]) : "r"(kb[8 + i]));
    stsm4(ka, kb[0], kb[1], kb[2], kb[3]); stsm4(ka + 2560, kb[4], kb[5], kb[6], kb[7]);
  };
  auto chores = [&](int s, int w4) __attribute__((always_inline)) {
    if (w4 == 1 || w4 == 2) {
      spin_coarse(lds4(bars + B_T + 4 + (s & 1) * 16) + d.c);
    }
    if (ATT && w4 == 2 && !(EXPT & 32)) send_qk(s);
    fetch_h1(s, w4);
  };
  if (tid == 0) STAMP(22);
  __syncwarp();
  mbar_wait(bars + B_RES, 0);
  mbar_wait(bars + B_H1, 0);
  if (tid == 0) STAMP(23);
  __syncwarp();
  auto gemv = [&](auto& gv, int s, auto wg_c, uint4& ta, uint2& tr, auto late) __attribute__((always_inline)) {
    constexpr int wg = decltype(wg_c)::value;
    BASES();
    TR(14);
    wait_ft(bars + B_M, s & 1);
    TR(0);
    uint32_t h0, h1;
    gv.template run<0>(w, l16 + A_MEM + wg * 8192, [&](auto nc) __attribute__((always_inline)) {
      constexpr int N = decltype(nc)::value;
      if (N == CK0) ta = lds16v(t16 + A_TAB);
      if (N == CK0 + 1) { h0 = lds4v(ta.x); h1 = lds4v(ta.x + 8192); }
      if (N == CK0 + 2) {
        const uint32_t tg = (s & 1) << 16;
        asm volatile("{.reg .pred p; setp.ne.u32 p, %1, 0; @p st.shared.u32 [%0], %2;}" ::"r"(bars + B_CHK), "r"(((h0 ^ tg) | (h1 ^ tg)) & TAG), "r"(s) : "memory");
      }
      if (N == LN) {
        tr = lds8v(t16 + A_TAB + 8192);
        late();
        if (PINA) HERE(ta.y);
      }
    });
  };
  auto scores = [&](const uint4& ta, const uint2& tr, const uint32_t* kb) __attribute__((always_inline)) {
    BASES();
    float sp[4][4];
    uint32_t a[16];
    const uint32_t chk = lds4v(bars + B_CHK + (t16 & zero));
#pragma unroll
    for (int i = 0; i < 4; i++) ldm(a + 4 * i, l16 + A_QM + i * 512);
#pragma unroll
    for (int i = 0; i < 4; i++) MMA_XZ(sp[i], a + 4 * i, kb[2 * i], kb[2 * i + 1]);
    const float x = (((sp[0][0] + sp[0][2]) + (sp[1][0] + sp[1][2])) + (sp[2][0] + sp[2][2])) + (sp[3][0] + sp[3][2]);
    const float y = (((sp[0][1] + sp[0][3]) + (sp[1][1] + sp[1][3])) + (sp[2][1] + sp[2][3])) + (sp[3][1] + sp[3][3]);
    st_async8(chk ? t16 + A_PQ : tr.x, x, y, chk ? bars : tr.y);
    sts8f(ta.w, x, y);
    return chk;
  };
  auto repair = [&](auto& gv, int s) __attribute__((always_inline)) {
    CNT(0);
    BASES();
    uint4 v[4];
    const char* src = G + (near + ((t16 - SB0) & 0xFF0));
    for (int it = 0;; it++) {
      uint32_t c = 0;
#pragma unroll
      for (int i = 0; i < 4; i++) v[i] = ld_tagged16(src + wpage(L_MEM + i));
#pragma unroll
      for (int i = 0; i < 4; i++) chk2(c, v[i], (s & 1) << 16);
      if (!__any_sync(~0u, c & TAG)) break;
      if (it > POLL_LIMIT) FAIL(2000);
    }
#pragma unroll
    for (int i = 0; i < 4; i++) sts16(t16 + A_MEM + i * 4096, v[i]);
    gv.prefetch(lds4(t16 + A_TAB + 8204));
    bar_sync(14, 256);
    sts4f(bars + B_CHK, 0.f);
    bar_sync(14, 256);
  };
  if (wg == 0) {
    bar_arrive(3, 256);
#pragma unroll 1
    for (int s = UNI(zero - 1);;) {
      GemvQK<2> gv;
      const int s1 = UNI(s + 1);
      proj(s, gv, IntC<0>(), [&](auto pre) __attribute__((always_inline)) { pre(0); wait_ft(bars + B_H0, (s + 1) & 1); TR(5); },
           [&]() __attribute__((always_inline)) {
        if (w4 == 2 && s >= 0) {
          const uint4 pl = lds16(bars + B_T + (s & 1) * 16);
          spin_coarse(pl.y + LOOKD * 5);
          const char* fl = flag_ptr(G, near, t16_, s);
          sts16(bars + B_T + (~s & 1) * 16, next_plan(pl, last_stores(ld_relaxed16(fl), fl, s), s, d));
          bar_arrive(6, 64);
        }
      }, []() {}, []() {}, []() {});
      if (s >= 0) TRD(cta);
      s = s1;
      uint4 tb, v0, v1, tu4;
      float4 p0, p1, p2;
      uint2 va, vb;
      const char *vxp, *vmp;
#pragma unroll 1
      for (;;) {
        uint4 ta;
        uint2 tr;
        uint32_t kb[8];
        gemv(gv, s, IntC<0>(), ta, tr, [&]() __attribute__((always_inline)) {
          ldm(kb, ta.z); ldm(kb + 4, ta.z + 2560);
        });
        gv.store(ta.y);
        tb = lds16v(t16_ + A_TAB + 4096);
        TR(1);
        bar_sync(7, 256);
        const uint32_t chk = scores(ta, tr, kb);
        TR(3);
        bar_sync(9, 192);
        BASES();
        p0 = lds16fv(l16 + A_SB); p1 = lds16fv(l16 + A_SB + 512); p2 = lds16fv(l16 + A_SB + 1024);
        tu4 = lds16v(t16 + A_TAB + 12288);
        vxp = ptr64(tb.z + (s & 1) * 16384, tb.w);
        v0 = ld_tagged16(vxp); v1 = ld_tagged16(vxp + 512);
        vmp = ptr64(tb.x, tb.y);
        va = ld_tagged8(vmp); vb = ld_tagged8(vmp + 1024);
        if (__builtin_expect(!__any_sync(~0u, chk), 1)) break;
        repair(gv, s);
      }
      BASES();
      const uint32_t l8 = ((l16 >> 1) + ((sb >> 1) + A_SB + 1536)) | (tu4.x & zero);
      p0.x *= SCL; p0.y *= SCL; p0.z *= SCL; p0.w *= SCL; p1.x *= SCL; p1.y *= SCL; p1.z *= SCL; p1.w *= SCL; p2.x = (p2.x + p2.z) * SCL; p2.y = (p2.y + p2.w) * SCL;
      wait_ft(bars + B_PAIR, s & 1);
      TR(4);
      float sc[10];
      {
        const float2 q4 = lds8f(l8 + 1024), q5 = lds8f(l8 + 1280), q0 = lds8f(l8), q1 = lds8f(l8 + 256), q2 = lds8f(l8 + 512), q3 = lds8f(l8 + 768);
        sc[0] = fmaf(q0.x, SCL, p0.x); sc[1] = fmaf(q0.y, SCL, p0.y); sc[2] = fmaf(q1.x, SCL, p0.z); sc[3] = fmaf(q1.y, SCL, p0.w);
        sc[4] = fmaf(q2.x, SCL, p1.x); sc[5] = fmaf(q2.y, SCL, p1.y); sc[6] = fmaf(q3.x, SCL, p1.z); sc[7] = fmaf(q3.y, SCL, p1.w);
        sc[8] = fmaf(q5.x, SCL, fmaf(q4.x, SCL, p2.x)); sc[9] = fmaf(q5.y, SCL, fmaf(q4.y, SCL, p2.y));
      }
      exp10v(sc);
      uint32_t p[5];
#pragma unroll
      for (int i = 0; i < 5; i++) p[i] = pack_bf16(sc[2 * i], sc[2 * i + 1]);
      const uint32_t tu = (~s & 1) << 16, tx = (~s & 2) << 15;
      auto pv = [&](bool ok) __attribute__((always_inline)) {
        float o0[4], o1[4], os[4], m0[4], m1[4];
        const uint32_t j0 = junk(), j1 = junk(), j2 = junk(), j3 = junk(), j4 = junk();
        mma_z(os, p[0], j0, p[1], j1, ONE2, ONE2); mma_z(o0, p[0], j0, p[1], j1, v0.x, v0.y); mma_z(o1, p[0], j0, p[1], j1, v1.x, v1.y);
        mma16816(os, p[2], j2, p[3], j3, ONE2, ONE2); mma16816(o0, p[2], j2, p[3], j3, v0.z, v0.w); mma16816(o1, p[2], j2, p[3], j3, v1.z, v1.w);
        mma1688(os, p[4], j4, ONE2);
        mma1688z(m0, p[4], j4, vb.x); mma1688z(m1, p[4], j4, vb.y);
        mma1688(o0, p[4], j4, va.x); mma1688(o1, p[4], j4, va.y);
        const float inv = rcp_fast(os[0]);
        const uint32_t u0 = pack_tag((o0[0] + m0[0]) * inv, (o0[1] + m0[1]) * inv, tu), u1 = pack_bf16((o1[0] + m1[0]) * inv, (o1[1] + m1[1]) * inv);
        st_tagged8_if(ptr64(tu4.x, tu4.y), u0, u1, ok);
        st_tagged8_if(ptr64(tu4.z, tu4.w), u0, u1, ok);
      };
      if (EXPT & 2) { v0.x = tx; v1.x = tx; }
      const bool bad = __any_sync(~0u, ((va.x ^ tu) | (vb.x ^ tu) | (v0.x ^ tx) | (v1.x ^ tx)) & TAG);
      pv(!bad);
      if (__builtin_expect(bad, 0)) {
        CNT(1);
        int it = 0;
        do {
          v0 = ld_tagged16(vxp); v1 = ld_tagged16(vxp + 512);
          va = ld_tagged8(vmp); vb = ld_tagged8(vmp + 1024);
          if (EXPT & 2) { v0.x = tx; v1.x = tx; }
          if (++it > POLL_LIMIT) FAIL(3000 + s);
        } while (__any_sync(~0u, ((va.x ^ tu) | (vb.x ^ tu) | (v0.x ^ tx) | (v1.x ^ tx)) & TAG));
        pv(true);
      }
      if (s == NSEG - 1) break;
      bar_arrive(3, 256);
      TR(7);
      bar_sync(1, 128);
      if (w4 == 1) {
        const uint32_t c0 = clk32();
        st_relaxed4_if(ptr64(plo(G) + ((wpage(L_FLAG) ^ ((t16 & 16) << 8)) + ((s & 1) * 512 + head * 16 + r * 4)), phi(G)),
                       ((c0 * 5 + time_offset(t16 & zero)) & ~31u) | (s & 31), (t16 & 0x1E0) == 0);
      }
    }
  } else {
#pragma unroll 1
    for (int s = UNI(zero - 1);;) {
      GemvQK<NPRE> gv;
      const int s1 = UNI(s + 1), ro = s < 0 ? w4 + 4 : w4;
      auto pace = [&]() __attribute__((always_inline)) {
        if (ro == 3) {
          bar_sync(6, 64);
          const uint32_t tm = lds4(bars + B_T + (~s & 1) * 16), tk = approach(tm, t16_ & zero);
          TRK(tk);
          fetch_mem(0, [&]() __attribute__((always_inline)) { spin_until(tm, tk); TR(12); });
        }
        if (ro == 7) {
          start_wait(bars + B_EP);
          fetch_mem(16384, []() {});
        }
      };
      proj(s, gv, IntC<1>(), [&](auto pre) __attribute__((always_inline)) {
        if (ro == 3) expect(bars + B_M, 16384);
        if (ro == 0) wait_ft(bars + B_H1 + ((s + 1) & 1) * 8, ((s + 1) >> 1) & 1);
        if (ro == 1) { wait_ft(bars + B_XE, s & 1); if (H0POS == 1) fetch_x(A_X, B_H0, s + 1, 0); }
        wait_ft(bars + B_PAIR, s & 1);
        const uint32_t c0 = clk32();
        if (ro == 1) { if (H0POS == 0) fetch_x(A_X, B_H0, s + 1, 0); expect(bars + B_PAIR, 1536); }
        spin_until((c0 + QUIET) * 5, 0);
        pre(0);
        if (ATT && ro == 2) sum_km();
        TR(6);
        bar_sync(3, 256);
        TR(7);
      }, [&]() __attribute__((always_inline)) {
      }, [&]() __attribute__((always_inline)) {
        if (ATT && ro == 2) { asm volatile("fence.proxy.async.shared::cta;" ::: "memory"); __syncwarp(); }
        if (CHPOS == 0) chores(s, ro);
      }, [&]() __attribute__((always_inline)) {
        if (CHPOS == 1) chores(s, ro);
        if (ATT && ro == 2) sent_qk();
        if (PACE == 2) pace();
      }, [&]() __attribute__((always_inline)) { if (PACE == 3) pace(); });
      if (KEEP && ro == 0) {
#pragma unroll 1
        for (int it = 0; it < 4096; it++) {
          const uint32_t t0 = lds4v(bars + B_T + (s & 1) * 16), t1 = lds4v(bars + B_T + (~s & 1) * 16);
          if (__any_sync(~0u, t1 - t0 < (1u << 31) && (int)(gtime() * 9 - t1) > 0)) break;
          float e[4];
          mma1688z(e, t0, t0, t0);
          sts4f(bars + B_EP + 4, e[0]);
        }
      }
      if (s >= 0) TRD(cta);
      s = s1;
#pragma unroll 1
      for (;;) {
        uint4 ta;
        uint2 tr;
        gemv(gv, s, IntC<1>(), ta, tr, []() {});
        gv.store(ta.y);
        TR(1);
        bar_sync(7, 256);
        uint32_t chk;
        if (__builtin_expect(w4 < 2, 1)) {
          uint32_t kb[8];
          ldm(kb, ta.z); ldm(kb + 4, ta.z + 512);
          chk = scores(ta, tr, kb);
          bar_arrive(9, 192);
        } else {
          chk = lds4v(bars + B_CHK);
          if (w4 == 3 && s < NSEG - 1 && !__any_sync(~0u, chk)) {
            expect(bars + B_H0, 32768);
            arrive_all(CS, t16_, A_BARS + B_XE);
            if (H0POS == 2) { wait_ft(bars + B_XE, s & 1); fetch_x(A_X, B_H0, s + 1, 0); }
          }
        }
        TR(3);
        if (__builtin_expect(!__any_sync(~0u, chk), 1)) break;
        repair(gv, s);
      }
      if (s == NSEG - 1) break;
    }
  }
  if (warp == 6) {
    sum_km();
    asm volatile("fence.proxy.async.shared::cta;" ::: "memory");
    __syncwarp();
    send_qk(NSEG - 1);
    sent_qk();
    if (lane < 2) st_relaxed4(G + (wpage(L_FLAG) ^ (lane << 12)) + 512 + head * 16 + r * 4, (NSEG - 1) & 31);
  }
  mbar_wait(bars + B_PAIR, (NSEG - 1) & 1);
  __syncwarp();
  cluster_sync();
  if (tid == 0) STAMP(CS > 2 ? 10 : 13);
  if (blockIdx.x == 0) asm volatile("griddepcontrol.wait;" ::: "memory");
}
__global__ void __launch_bounds__(256, 1)
qk_kernel(const __grid_constant__ CUtensorMap tmWq, const __grid_constant__ CUtensorMap tmWk, const __grid_constant__ CUtensorMap tmX,
          char* __restrict__ G, const Pace d, int zero, int cta0, int cs) {
  qk_body(tmWq, tmWk, tmX, G, d, zero, blockIdx.x + cta0, cs);
}

constexpr int V_WV = 0;
constexpr int V_WO = 32768;
constexpr int V_X = 65536;
constexpr int V_MEM = V_X + 65536;
constexpr int V_U = V_MEM + 16384;
constexpr int V_EX = V_U + 32768;
constexpr int V_VT = V_EX + EX_BYTES;
constexpr int V_OUT = V_VT + 4 * 6144;
constexpr int V_TAB = V_OUT + 4096;
constexpr int V_BARS = V_TAB + 2048;
constexpr int V_RB = V_BARS + 512;
constexpr int V_TB3 = V_RB + 512;
constexpr int V_TRC = V_TB3 + 512;
constexpr int V_ONE = V_TRC + 512;
constexpr int V_SMEM = V_ONE + 384;
constexpr int C_XF = 80  , C_XE = 96  , C_M = 112, C_EXR = 120, C_U = 128  , C_EX = 144, C_EXE = 152, C_T = 160  , C_NEAR = 176, C_TK = 192;
#define VPIN 0
#define VLB 3
#define PF1 1
#define PF0 3
#define OLA 4
#define UPOS 1
#define OPOS 1
#define VDEP 1
#define SSF 24
#define B6 1
#define PVG 1
#define VC0 3
#define VC1 7
#define VC2 11
#define EXPOS 1
#define VPRE 4
#define VLA 3
#define UW 3
#define RDLY 0
#define VB 0
#define XV 32
#define X0POS 2

#define ACC8(d, o) "+f"(d[o]), "+f"(d[o + 1]), "+f"(d[o + 2]), "+f"(d[o + 3]), "+f"(d[o + 4]), "+f"(d[o + 5]), "+f"(d[o + 6]), "+f"(d[o + 7])
#define OUT8(d, o) "=f"(d[o]), "=f"(d[o + 1]), "=f"(d[o + 2]), "=f"(d[o + 3]), "=f"(d[o + 4]), "=f"(d[o + 5]), "=f"(d[o + 6]), "=f"(d[o + 7])
#define R20 "{%0,%1,%2,%3,%4,%5,%6,%7,%8,%9,%10,%11,%12,%13,%14,%15,%16,%17,%18,%19}"
#define R32 "{%0,%1,%2,%3,%4,%5,%6,%7,%8,%9,%10,%11,%12,%13,%14,%15,%16,%17,%18,%19,%20,%21,%22,%23,%24,%25,%26,%27,%28,%29,%30,%31}"
template <int ACC> __device__ __forceinline__ void wg_ss40(float* d, uint64_t da, uint64_t db) {
  if (ACC) asm volatile("wgmma.mma_async.sync.aligned.m64n40k16.f32.bf16.bf16 " R20 ", %20, %21, 1, 1, 1, 0, 0;"
                        : ACC8(d, 0), ACC8(d, 8), "+f"(d[16]), "+f"(d[17]), "+f"(d[18]), "+f"(d[19]) : "l"(da), "l"(db));
  else asm volatile("wgmma.mma_async.sync.aligned.m64n40k16.f32.bf16.bf16 " R20 ", %20, %21, 0, 1, 1, 0, 0;"
                    : OUT8(d, 0), OUT8(d, 8), "=f"(d[16]), "=f"(d[17]), "=f"(d[18]), "=f"(d[19]) : "l"(da), "l"(db));
}
template <int ACC> __device__ __forceinline__ void wg_rs64(float* d, uint32_t a0, uint32_t a1, uint32_t a2, uint32_t a3, uint64_t db) {
  if (ACC) asm volatile("wgmma.mma_async.sync.aligned.m64n64k16.f32.bf16.bf16 " R32 ", {%32,%33,%34,%35}, %36, 1, 1, 1, 0;"
                        : ACC8(d, 0), ACC8(d, 8), ACC8(d, 16), ACC8(d, 24) : "r"(a0), "r"(a1), "r"(a2), "r"(a3), "l"(db));
  else asm volatile("wgmma.mma_async.sync.aligned.m64n64k16.f32.bf16.bf16 " R32 ", {%32,%33,%34,%35}, %36, 0, 1, 1, 0;"
                    : OUT8(d, 0), OUT8(d, 8), OUT8(d, 16), OUT8(d, 24) : "r"(a0), "r"(a1), "r"(a2), "r"(a3), "l"(db));
}

template <int ACC> __device__ __forceinline__ void wg_rs8(float* d, uint32_t a0, uint32_t a1, uint32_t a2, uint32_t a3, uint64_t db) {
  if (ACC) asm volatile("wgmma.mma_async.sync.aligned.m64n8k16.f32.bf16.bf16 {%0,%1,%2,%3}, {%4,%5,%6,%7}, %8, 1, 1, 1, 0;"
                        : "+f"(d[0]), "+f"(d[1]), "+f"(d[2]), "+f"(d[3]) : "r"(a0), "r"(a1), "r"(a2), "r"(a3), "l"(db));
  else asm volatile("wgmma.mma_async.sync.aligned.m64n8k16.f32.bf16.bf16 {%0,%1,%2,%3}, {%4,%5,%6,%7}, %8, 0, 1, 1, 0;"
                    : "=f"(d[0]), "=f"(d[1]), "=f"(d[2]), "=f"(d[3]) : "r"(a0), "r"(a1), "r"(a2), "r"(a3), "l"(db));
}

struct GemvV {
  float a[4], b[4], a2[4], b2[4];
  uint4 m[16];
  uint32_t pp[4][8], z0, c, tg;
  static __device__ __forceinline__ constexpr int blk(int n) { return (n + 12) & 15; }
  static __device__ __forceinline__ constexpr int lm(int n) {
    const int a = n + 1 + VLA + (n < 2 ? 0 : n - 1 > VLB ? VLB : n - 1);
    return a > 16 ? 16 : a;
  }
  __device__ __forceinline__ uint32_t prefetch(uint32_t ws) {
    uint32_t y = ~0u;
#pragma unroll
    for (int j = 0; j < 8; j++) { ldw(pp[j >> 1] + (j & 1) * 4, ws + j * 2048); y &= pp[j >> 1][(j & 1) * 4]; }
    return y;
  }
  __device__ __forceinline__ void first(uint32_t mb) {
#pragma unroll
    for (int n = 0; n < lm(-1); n++) m[n] = lds16v(mb + blk(n) * 512);
  }
  template <int N, int END, typename F> __device__ __forceinline__ void run(const uint32_t* w, uint32_t mb, F hook) {
    if constexpr (N < END) {
      const uint32_t* p = N < 4 ? pp[N & 3] : w + 96 + blk(N) * 8;
      float* d0 = (N & 1) ? a2 : a;
      float* d1 = (N & 1) ? b2 : b;
      if (N < 2) MMA_XZ(d0, p, m[N].x, m[N].y); else MMA_X(d0, p, m[N].x, m[N].y);
      hook(IntC<2 * N>());
      if (VDEP == 2) { c |= m[N].x ^ tg; m[N].z |= c & z0; }
      if (N < 2) MMA_XZ(d1, p + 4, m[N].z, m[N].w); else MMA_X(d1, p + 4, m[N].z, m[N].w);
      if (VDEP < 2) c |= m[N].x ^ tg;
#pragma unroll
      for (int n = lm(N - 1); n < lm(N); n++) m[n] = lds16v((VDEP == 1 ? mb | (c & z0) : mb) + blk(n) * 512);
      hook(IntC<2 * N + 1>());
      run<N + 1, END>(w, mb, hook);
    }
  }
  static constexpr int CV = 31;
};

#undef TKA
#define TKA (bars + C_TK)
template <int CS>
__device__ __forceinline__ void vo_body(const CUtensorMap& tmWv, const CUtensorMap& tmWo, const CUtensorMap& tmX, const CUtensorMap& tmU, const bf16* __restrict__ mem0,
                                        const bf16* __restrict__ xin, char* __restrict__ G, const Pace d, int zero, int block) {
  extern __shared__ __align__(1024) uint8_t smem_raw[];
  const uint32_t sb = smem_u32(smem_raw);
  if ((sb & 0x3FFFF) != SB0) __trap();
  asm volatile("griddepcontrol.launch_dependents;" ::: "memory");
  const int tid = threadIdx.x, t7 = tid & 127, lane = tid & 31;
  const int warp = UNI(tid >> 5), wg = warp >> 2, w4 = warp & 3;
  const uint32_t wofs = UNI((tid >> 5) * -512);
  const int cta = UNI(block), r = cta & 1, head = cta >> 1, fcol = cta * 64, rank = cta & (CS - 1);
  constexpr uint32_t ALL = (1u << CS) - 1;
  const uint32_t bars = sb + V_BARS;
  const uint32_t trc = UNI(sb + V_TRC + (tid >> 5) * 64); (void)trc;
  if (tid == 0) {
    STAMP(0);
    for (int i = 0; i < 9; i++) mbar_init(bars + i * 8, 1);
    asm volatile("fence.mbarrier_init.release.cluster;" ::: "memory");
#pragma unroll 1
    for (int i = 0; i < 16; i++) {
      if (!(i & 1)) mbar_expect_tx(bars + (i >> 1) * 8, 16384);
      tma2d(sb + V_X + i * 8192, &tmWo, head * 32, r * 2048 + i * 128, bars + (i >> 1) * 8);
    }
    mbar_expect_tx(bars + B_RES, 49152);
    tma2d_ef(sb + V_X + 8 * 16384, &tmWv, fcol, 0, bars + B_RES);
    for (int i = 0; i < 2; i++) tma2d_ef(sb + V_WV + i * 16384, &tmWv, fcol, i * 512 + 384, bars + B_RES);
    for (int i = 9; i < 20; i++) mbar_init(bars + i * 8, i * 8 == C_XE ? 4 * CS : i * 8 == C_XE + 8 ? 3 * CS : i * 8 == C_EXE ? 8 : 1);
    asm volatile("fence.mbarrier_init.release.cluster;" ::: "memory");
    sts8f(bars + C_NEAR, __uint_as_float(~0u), __uint_as_float(~0u));
  }
  if (tid == 64) asm volatile("cp.async.bulk.prefetch.L2.global [%0], %1;" ::"l"(xin + cta * (XP * 512)), "n"(XP * 1024) : "memory");
  const uint32_t gm = wpage(L_MEM + (head >> 3)) + (head & 7) * 512 + r * 256;
  {
    const uint4 z = make_uint4(0, 0, 0, 0);
    *reinterpret_cast<uint4*>(G + ((wpage(L_VM + head) + r * 2048 + t7 * 16) ^ (wg << 12))) = z;
    if (tid < 4) *reinterpret_cast<uint32_t*>(G + (wpage(L_FLAG) ^ ((tid & 1) << 12)) + (tid >> 1) * 512 + head * 16 + 8 + r * 4) = 0;
    for (int i = 0; i < 4; i++) *reinterpret_cast<uint4*>(G + ((wpage(cta) ^ ((i & 1) << 12)) + VX0 + (i >> 1) * 16384 + tid * 16)) = z;
    probe_init(G, 512 + cta * 8);
    if (tid < 64) {
      const uint32_t* m0 = reinterpret_cast<const uint32_t*>(mem0) + (4 * r + (lane >> 3)) * (DM / 2) + head * 16 + (lane & 1) * 8 + ((lane & 7) >> 1);
      char* p = G + ((gm + lane * 8) ^ (warp << 12));
      *reinterpret_cast<uint2*>(p) = make_uint2(0, 0);
      *reinterpret_cast<uint2*>(p + 16384) = make_uint2(m0[0], m0[4]);
    }
  }
  __syncthreads();
  const int lk = (lane & 7) + ((lane >> 4) << 3);
  const uint32_t wt_off = lk * 128 + (((((tid >> 4) & 6) + ((lane >> 3) & 1)) ^ (lk & 7)) << 4);
  const int g = lane >> 2, c = lane & 3;
  uint32_t w[192];
  const uint32_t t16_ = OPQ(sb + tid * 16);
  mbar_wait(bars + warp * 8, 0);
  {
    const int rr = lane & 7, mi = lane >> 3, cc = rr >> 1;
    const uint32_t a = sb + V_X + (tid >> 5) * 16384 + ((cc >> 1) * 16 + (cc & 1) * 4 + (mi >> 1) * 8 + (rr & 1)) * 64 + (mi & 1) * 16;
#pragma unroll
    for (int q = 0; q < 32; q++) {
      const uint32_t aq = a + ((q >> 2) * 32 + (q & 2)) * 64 + (q & 1) * 32;
      if (q < 8) { uint32_t f[4]; ldw(f, aq); sts16(t16_ + V_WO + q * 4096, make_uint4(f[0], f[1], f[2], f[3])); }
      else ldw(w + q * 4 - 32, aq);
    }
  }
  landed_all<96>(w, zero);
  __syncthreads();
  if (tid == 0)
#pragma unroll 1
    for (int i = 5; i > 0; i--) {
      mbar_expect_tx(bars + i * 8, 16384);
      tma2d_ef(sb + V_X + (i == 1 ? 0 : i + 2) * 16384, &tmWv, fcol, (i / 3) * 512 + (i % 3) * 128, bars + i * 8);
    }
  if (lane == 0) probe_near(G, 512 + cta * 8 + (tid >> 5), bars + C_NEAR);
  __syncwarp();
  cluster_sync_relaxed();
  if (tid == 0) STAMP(21);
  const uint32_t near = pick_near(CS, V_BARS + C_NEAR);
  const uint32_t rdelta = UNI(mapa(sb, rank ^ 1) - sb);
  uint32_t vxo, vmo;
  sts8f(sb + V_TAB + tid * 8, __uint_as_float(sb + V_WV + (tid >> 7) * 16384 + wt_off),
        __uint_as_float(sb + V_VT + (((tid >> 4) & 4) + ((lane & 7) >> 1)) * 768 + (((tid >> 3) & 4) + (lane & 1)) * 16));
  if (tid < 96) sts4f(sb + V_ONE + tid * 4, __uint_as_float(tid < 64 ? ONE2 : 0));
  if (tid < 32) {
    const char* mp = G + ((gm ^ near ^ 4096) + lane * 8);
    sts16(t16_ + V_TB3, make_uint4(plo(mp), phi(mp), plo(mp) ^ 4096, phi(mp)));
  }
  const uint32_t tabo = UNI((sb >> 1) + V_TAB);
  auto TAB = [&](uint32_t t) __attribute__((always_inline)) {
    uint32_t a; asm volatile("{.reg .u32 x; shr.u32 x, %1, 1; add.u32 %0, x, %2;}" : "=r"(a) : "r"(t), "r"(tabo)); return a;
  };
  if (warp == 0) { sts16(bars + C_T, make_uint4(0, 0, d.u0, d.m0)); }
  auto fetch_x = [&](int n, int h) __attribute__((always_inline)) {
    if (n > 0) wait_ft(bars + C_XE + h * 8, (n - 1) & 1);
    expect(bars + C_XF + h * 8, 32768);
    issue_x(&tmX, sb + V_X + h * 32768 + rank * (32768 / CS), bars + C_XF + h * 8, n, h * 8 + rank * (8 / CS), ALL);
  };
  auto release_x = [&](int h) __attribute__((always_inline)) { arrive_all(CS, t16_, V_BARS + C_XE + h * 8); };
  auto fetch_mem = [&](uint32_t slot) __attribute__((always_inline)) { fetch_mem_mc<CS>(sb + V_MEM, G, near + slot, rank, bars + C_M); };
  auto fetch_ex = [&](int n) __attribute__((always_inline)) {
    {
      if (n > 0) wait_ft(bars + C_EXE, (n - 1) & 1);
      expect(bars + C_EX, EX_BYTES);
      const char* src = reinterpret_cast<const char*>(g_rings.ex[n & 3]) + head * EX_BYTES;
      const uint32_t dst = sb + V_EX;
      if (r != head >> 4) { }
      else if (rank < 2) bulk_mc<3>(dst, src, EX_BYTES, bars + C_EX);
      else if (rank < 4) bulk_mc<12>(dst, src, EX_BYTES, bars + C_EX);
      else if (rank < 6) bulk_mc<48>(dst, src, EX_BYTES, bars + C_EX);
      else bulk_mc<192>(dst, src, EX_BYTES, bars + C_EX);
    }
    __syncwarp();
  };
  auto release_ex = [&]() __attribute__((always_inline)) {
    BASES();
    if ((t16 & 0x1E0) == 0) mbar_arrive_cluster(mapa(SB0 + V_BARS + C_EXE, ((t16 >> 4) & 1) ^ rank));
    __syncwarp();
  };
  auto vproj1 = [&](int n, GemvV& gv, uint32_t ws) __attribute__((always_inline)) {
    float d[16];
    wait_ft(bars + C_XF + 8, n & 1);
    bar_sync(6, 160);
    gv.prefetch(ws);
    WG_FENCE();
#pragma unroll
    for (int k = 0; k < XV; k++) {
      const uint64_t b = cdesc(0, V_X + 32768 + xk(k));
      if (k == 0) wg_rs32<0>(d, w + 96, b);
      else if (k < 24) wg_rs32<1>(d, w + 96 + k * 4, b);
      else wg_rs32<1>(d, gv.pp[(k - 24) >> 1] + (k & 1) * 4, b);
    }
    WG_COMMIT();
    WG_WAIT(0);
    acc_fence16(d);
#pragma unroll
    for (int i = 0; i < 4; i++) sts16f(t16_ + (V_X + 32768 - 2048) + i * 2048, d[4 * i], d[4 * i + 1], d[4 * i + 2], d[4 * i + 3]);
  };
  auto vproj0 = [&](int n, auto mid, auto last) __attribute__((always_inline)) {
    float d[16];
#pragma unroll
    for (int i = 0; i < 4; i++) {
      const float4 p = lds16f(t16_ + V_X + 32768 + i * 2048);
      d[4 * i] = p.x; d[4 * i + 1] = p.y; d[4 * i + 2] = p.z; d[4 * i + 3] = p.w;
    }
    acc_fence16(d);
    WG_FENCE();
#pragma unroll
    for (int kk = 0; kk < XV; kk++) {
      const int k = (kk + SSF) & 31;
      const uint64_t b = cdesc(0, V_X + xk(k));
      if (k < 24) wg_rs32<1>(d, w + 96 + k * 4, b);
      else wg_ss32(d, cdesc(0, V_WV + (k - 24) * 2048), b);
    }
    WG_COMMIT();
    if (w4) release_x(1);
    mid();
    BASES();
    const uint32_t vt = lds4(TAB(t16) + 4) + (n & 3) * 6144 + (t16 & 384);
    const uint32_t tx = (~n & 2) << 15;
    WG_WAIT(0);
    acc_fence16(d);
    const uint4 f0 = make_uint4(pack_tag(d[0], d[1], tx), pack_bf16(d[4], d[5]), pack_bf16(d[8], d[9]), pack_bf16(d[12], d[13]));
    const uint4 f1 = make_uint4(pack_tag(d[2], d[3], tx), pack_bf16(d[6], d[7]), pack_bf16(d[10], d[11]), pack_bf16(d[14], d[15]));
    char* dst = ptr64(t16 + (vxo + (n & 1) * 16384), phi(G));
    st_tagged16(dst, f0); st_tagged16(dst + 512, f1);
    last();
    if (ATT) { stsm4(vt + (clk32() & zero), pack_bf16(d[0], d[1]), f0.y, f0.z, f0.w); stsm4(vt + 32, pack_bf16(d[2], d[3]), f1.y, f1.z, f1.w); }
    release_x(0);
  };
  auto attention = [&](int n, bool gate) __attribute__((always_inline)) {
    float sa[20];
    WG_FENCE();
#pragma unroll
    for (int k = 0; k < 8; k++) {
      const int o = V_EX + (k >> 2) * EX_CTA;
      const uint64_t da = ndesc(0, o + (k & 3) * 1024, 128, 128), db = ndesc(0, o + EX_K + (k & 3) * 1280, 640, 128);
      if (k == 0) wg_ss40<0>(sa, da, db); else wg_ss40<1>(sa, da, db);
    }
    WG_COMMIT();
    BASES();
    const int row = (int)(((t16 - SB0) >> 6) & 31);
    const int dlt = row - (int)((t16 >> 3) & 6);
    WG_WAIT(0);
    asm volatile("" : ACC8(sa, 0), ACC8(sa, 8), "+f"(sa[16]), "+f"(sa[17]), "+f"(sa[18]), "+f"(sa[19])::"memory");
    release_ex();
    float sc[10];
#pragma unroll
    for (int i = 0; i < 8; i++) sc[i] = dlt >= (i >> 1) * 8 + (i & 1) ? sa[(i >> 1) * 4 + (i & 1)] * SCL : -INFINITY;
    sc[8] = sa[16] * SCL; sc[9] = sa[17] * SCL;
    exp10v(sc);
    uint32_t p[5];
#pragma unroll
    for (int i = 0; i < 5; i++) p[i] = pack_bf16(sc[2 * i], sc[2 * i + 1]);
    float o[32];
    const uint32_t z = (n & 3) * 384;
    const uint32_t j0 = junk(), j1 = junk(), j2 = junk(), j3 = junk(), j4 = junk(), j5 = junk();
    uint32_t p5 = p[4];
    keep32(p5);
    float os[4];
    if (PVG && gate) bar_sync(7, 160);
    WG_FENCE();
    wg_rs64<0>(o, p[0], j0, p[1], j1, ndesc(z, V_VT, 128, 768));
    wg_rs8<0>(os, p[0], j0, p[1], j1, ndesc(0, V_ONE, 128, 128));
    wg_rs64<1>(o, p[2], j2, p[3], j3, ndesc(z, V_VT + 256, 128, 768));
    wg_rs8<1>(os, p[2], j2, p[3], j3, ndesc(0, V_ONE, 128, 128));
    wg_rs64<1>(o, p[4], j4, p5, j5, ndesc(z, V_VT + 512, 128, 768));
    wg_rs8<1>(os, p[4], j4, p5, j5, ndesc(0, V_ONE + 128, 128, 128));
    WG_COMMIT();
    WG_WAIT(0);
    asm volatile("" : ACC8(o, 0), ACC8(o, 8), ACC8(o, 16), ACC8(o, 24)::"memory");
    asm volatile("" : "+f"(os[0]), "+f"(os[1]), "+f"(os[2]), "+f"(os[3])::"memory");
    const float inv = rcp_fast(os[0]);
    asm volatile("cp.async.bulk.wait_group.read 0;" ::: "memory");
    __syncwarp();
    const uint32_t oa = sb + V_OUT + row * 128 + (((t16 & 48) ^ (row << 4)) & 0x70);
    sts16(oa, make_uint4(pack_bf16(o[0] * inv, o[1] * inv), pack_bf16(o[4] * inv, o[5] * inv), pack_bf16(o[8] * inv, o[9] * inv), pack_bf16(o[12] * inv, o[13] * inv)));
    sts16(oa ^ 64, make_uint4(pack_bf16(o[16] * inv, o[17] * inv), pack_bf16(o[20] * inv, o[21] * inv), pack_bf16(o[24] * inv, o[25] * inv), pack_bf16(o[28] * inv, o[29] * inv)));
  };
  auto store_o = [&](int n) __attribute__((always_inline)) {
    asm volatile(ELECT "cp.async.bulk.tensor.2d.global.shared::cta.bulk_group [%0, {%2, %3}], [%1];}"
                 ::"l"(&tmU), "r"(sb + (V_OUT - 4096) - wofs * 2), "r"(fcol), "r"((n & 127) * SEG + w4 * 8) : "memory");
    asm volatile("cp.async.bulk.commit_group;" ::: "memory");
  };
  if (warp == 2) fetch_x(0, 1);
  if (tid == 32) { mbar_expect_tx(bars + B_PAIR, 512); start_arrive(bars + C_NEAR + 8); }
  __syncwarp();
  mbar_wait(bars + B_RES, 0);
#pragma unroll
  for (int i = 0; i < 3; i++) {
    if (i || wg) mbar_wait(bars + (wg * 3 + i) * 8, 1);
    const uint32_t a = sb + V_X + (wg ? 5 + i : i == 0 ? 8 : i == 1 ? 0 : 4) * 16384 + wt_off;
#pragma unroll
    for (int j = 0; j < 8; j++) ldw(w + 96 + (i * 8 + j) * 4, a + j * 2048);
  }
  landed_all<96>(w + 96, zero);
  cluster_sync_relaxed();
  if (tid == 0) STAMP(1);
  GemvV gv;
  auto reader_side = [&]() __attribute__((always_inline)) {
    uint32_t q;
    for (int it = 0; __any_sync(~0u, (q = ld_relaxed4(&g_rings.side[cta]) - lds4(bars + C_NEAR + 8)) > 1) && it < POLL_LIMIT; it++) { }
    vxo = UNI(plo(G) + (wpage(cta) ^ (q << 12)) + VX0 - wofs - sb);
    vmo = UNI(plo(G) + ((wpage(L_VM + head) ^ (q << 12)) + r * 2048) - (sb >> 1));
  };
  auto gemv_v = [&](int s, auto wg_c) __attribute__((always_inline)) {
    constexpr int wg = decltype(wg_c)::value;
    const uint32_t tg = (s & 1) << 16;
    uint32_t tv;
    gemv_mem<wg, V_MEM, false>(gv, w, s, t16_, wofs, near, G, [&](uint32_t t) __attribute__((always_inline)) { return TAB(t); }, bars + C_M, zero, trc,
                         [&](auto nc, bool) __attribute__((always_inline)) { if (decltype(nc)::value == 26) tv = lds4v(TAB(t16_ | (gv.m[14].x & zero)) + 4); });
#pragma unroll
    for (int i = 0; i < 4; i++) gv.a[i] = (gv.a[i] + gv.b[i]) + (gv.a2[i] + gv.b2[i]);
    const uint32_t m0 = pack_tag(gv.a[0], gv.a[1], tg ^ TAG), m1 = pack_bf16(gv.a[2], gv.a[3]);
    BASES();
    st_tagged8(ptr64(((t16 >> 1) + vmo), phi(G)), m0, m1);
    if (ATT) {
      const uint32_t vt = tv + (s & 3) * 6144 + (512 + wg * 128) + ((t16 >> 2) & 32);
      asm volatile("stmatrix.sync.aligned.m8n8.x2.shared.b16 [%0], {%1, %2};" ::"r"(vt), "r"(pack_bf16(gv.a[0], gv.a[1])), "r"(m1) : "memory");
    }
    TR(1);
    bar_sync(4, 256);
  };
  uint32_t w0[32], wsv;
  auto pre_o = [&]() __attribute__((always_inline)) {
#pragma unroll
    for (int i = 0; i < 8; i++) { const uint4 t = lds16v(t16_ + V_WO + i * 4096); w0[4 * i] = t.x; w0[4 * i + 1] = t.y; w0[4 * i + 2] = t.z; w0[4 * i + 3] = t.w; }
  };
  auto gemv_o = [&](int s, auto wg_c, auto look) __attribute__((always_inline)) {
    constexpr int wg = decltype(wg_c)::value;
    const uint32_t tu = (~s & 1) << 16;
    float a0[4], a1[4], a2[4], a3[4];
    uint4 uv[8];
    auto mul = [&](auto hook) __attribute__((always_inline)) {
#pragma unroll
      for (int i = 0; i < 8; i++) {
        const uint32_t* p = i < 2 ? w0 + 16 : w + (i * 16 - 32);
        if (i == 0) { MMA_XZ(a0, w0, uv[0].x, uv[0].y); MMA_XZ(a1, w0 + 4, uv[0].x, uv[0].y); MMA_XZ(a2, w0 + 8, uv[0].z, uv[0].w); MMA_XZ(a3, w0 + 12, uv[0].z, uv[0].w); }
        else { MMA_X(a0, p, uv[i].x, uv[i].y); MMA_X(a1, p + 4, uv[i].x, uv[i].y); MMA_X(a2, p + 8, uv[i].z, uv[i].w); MMA_X(a3, p + 12, uv[i].z, uv[i].w); }
        hook(i);
      }
    };
    BASES();
    const uint32_t ub = t16 + (V_U + wofs * -7);
    const uint32_t owr = (t16 & 48) * 16 + ((((t16 >> 2) & 0x60) ^ (t16 & 16) ^ ((t16 & 32) * 2)) | ((t16 >> 3) & 8)) + (sb + V_U + wofs * -8);
    landed(zero & owr & w0[0] & w0[4] & w0[8] & w0[12] & w0[16] & w0[20] & w0[24] & w0[28]);
    wait_ft(bars + C_U + wg * 8, s & 1);
    TR(4);
#pragma unroll
    for (int i = 0; i < OLA; i++) uv[i] = lds16v(ub + i * 512);
    uint32_t cc = 0;
    mul([&](int i) __attribute__((always_inline)) {
      cc |= uv[i].x ^ tu;
      if (i + OLA < 8) uv[i + OLA] = lds16v(ub + (i + OLA) * 512);
      if (i + OLA == 7) wsv = lds4v(TAB(t16));
      if (i == 3) look(uv[3].y & zero);
    });
    const bool bad = __any_sync(~0u, (int)(cc << 15) < 0);
    if (__builtin_expect(bad, 0)) {
      CNT(3);
      const char* src = G + ((wpage(L_U + r * 8 + warp) ^ near) + (t16 & 0x1F0));
      for (int it = 0;; it++) {
        uint32_t c2 = 0;
#pragma unroll
        for (int i = 0; i < 8; i++) uv[i] = ld_tagged16(src + i * 512);
#pragma unroll
        for (int i = 0; i < 8; i++) chk2(c2, uv[i], tu);
        if (!__any_sync(~0u, c2 & TAG)) break;
        if (it > POLL_LIMIT) FAIL(4000);
      }
#pragma unroll
      for (int i = 4; i < 8; i++) sts16(ub + i * 512, uv[i]);
      pre_o();
      mul([&](int i) __attribute__((always_inline)) { if (i < 4) uv[i + 4] = lds16v(ub + (i + 4) * 512); });
    }
    sts8f(owr, a0[0] + a2[0], a0[2] + a2[2]); sts8f(owr + 128, a0[1] + a2[1], a0[3] + a2[3]);
    sts8f(owr ^ 16, a1[0] + a3[0], a1[2] + a3[2]); sts8f((owr ^ 16) + 128, a1[1] + a3[1], a1[3] + a3[3]);
  };
  if (wg == 0) {
    if (w4 == 1) bar_arrive(6, 160);
    if (w4 == 0) { expect(bars + C_M, 16384); start_wait(bars + C_NEAR + 8); fetch_mem(16384); }
    reader_side();
    wait_ft(bars + C_XF, 0);
    bar_sync(4, 256);
#pragma unroll 1
    for (int s = UNI(zero - 1);;) {
      const int s1 = UNI(s + 1), ro = s < 0 ? 4 : w4;
      uint32_t tu = 0;
      auto do_u = [&](auto t_c) __attribute__((always_inline)) {
        constexpr int t = decltype(t_c)::value;
        auto fetch_u = [&](auto r_c) __attribute__((always_inline)) {
          constexpr int r = decltype(r_c)::value;
          spin_until(tu, 0);
          TR(12);
#pragma unroll
          for (int i = 0; i < 8 / CS; i++) {
            const int j = (rank >> 1) * (8 / CS) + i;
            const char* src = G + ((wpage(L_U + r * 8 + t * 4) ^ near) + ((j & 1) << 18) + ((j & 2) << 19));
            if (CS > 2) bulk_mc<(0x55u << r) & ALL>(sb + V_U + t * 16384 + j * 4096, src, 4096, bars + C_U + t * 8);
            else bulk(sb + V_U + t * 16384 + j * 4096, src, 4096, bars + C_U + t * 8);
          }
        };
        if (r) fetch_u(IntC<1>()); else fetch_u(IntC<0>());
      };
      vproj0(s + 1, [&]() __attribute__((always_inline)) {
        if (w4 == 2 && s + 2 < NSEG) fetch_x(s + 2, 1);
        if (ro == 2) { expect(bars + C_M, 16384); expect(bars + C_U, 16384); expect(bars + C_U + 8, 16384); }
        if (ro & 1) {
          tu = lds4(bars + C_T + 4);
          if (s == 0) { const char* fl = flag_ptr(G, near, t16_, 0); tu = last_stores(ld_relaxed16(fl), fl, 0).x; }
          LOGT(lds16(bars + C_T));
          tu += (ro == 1 ? d.s : 0) - time_offset(t16_ & zero);
        }
        if (PVG && ro == 0) bar_arrive(7, 160);
      }, [&]() __attribute__((always_inline)) { TR(2); if (ro == 3) do_u(IntC<1>()); });
      if (s < 0) {
        if (w4 == 1) bar_arrive(6, 160);
        wsv = lds4(TAB(t16_));
      } else {
      pre_o();
      if (w4 == 1) do_u(IntC<0>());
      uint4 f = make_uint4(0, 0, 0, 0);
      const char* fl = flag_ptr(G, near, t16_, s);
      gemv_o(s, IntC<0>(), [&](uint32_t z) __attribute__((always_inline)) { ld_relaxed16_if(f, ptr64(plo(fl) | z, phi(fl)), w4 == 0); });
      TR(5);
      BASES();
      const uint32_t tp = (r ^ 1) * 4 + w4;
      const uint32_t ra = (((t16 >> 2) & 0x7C) ^ ((tp & 2) << 3) ^ ((tp & 4) << 4)) + (sb + V_U + tp * 128);
      bar_sync(3, 256);
      {
        float p[8];
#pragma unroll
        for (int i = 0; i < 8; i++) p[i] = lds4f(ra + i * 4096);
        st_async4((t16 >> 2) + (sb - (sb >> 2) + V_RB + rdelta), (((p[0] + p[1]) + (p[2] + p[3])) + (p[4] + p[5])) + (p[6] + p[7]), bars + B_PAIR + rdelta);
      }
      TR(6);
      if (w4 == 1) {
        const uint32_t rb = ((t16 & 0x1F0) ^ ((t16 >> 4) & 16) ^ (r << 6)) + (sb + V_U + r * 512);
        float4 p[8];
#pragma unroll
        for (int i = 0; i < 8; i++) p[i] = lds16fv(rb + i * 4096);
        uint4 t3 = lds16v(t16 + (V_TB3 - 512));
        bar_arrive(6, 160);
        HERE(t3.z);
        float sm[4];
        sm[0] = ((p[0].x + p[1].x) + (p[2].x + p[3].x)) + ((p[4].x + p[5].x) + (p[6].x + p[7].x));
        sm[1] = ((p[0].y + p[1].y) + (p[2].y + p[3].y)) + ((p[4].y + p[5].y) + (p[6].y + p[7].y));
        sm[2] = ((p[0].z + p[1].z) + (p[2].z + p[3].z)) + ((p[4].z + p[5].z) + (p[6].z + p[7].z));
        sm[3] = ((p[0].w + p[1].w) + (p[2].w + p[3].w)) + ((p[4].w + p[5].w) + (p[6].w + p[7].w));
        wait_ft(bars + B_PAIR, s & 1);
        TR(7);
        const float4 q = lds16f(t16_ + (V_RB - 512));
        const uint32_t m0 = pack_tag(sm[0] + q.x, sm[2] + q.z, (~s & 1) << 16), m1 = pack_bf16(sm[1] + q.y, sm[3] + q.w);
        st_tagged8(ptr64(t3.x, t3.y), m0, m1);
        st_tagged8(ptr64(t3.z, t3.w), m0, m1);
        TR(8);
        const uint32_t c0 = clk32();
        if (PF0 == 3) bar_arrive(9, 96);
        st_relaxed4_if(G + ((wpage(L_FLAG) ^ ((t16 & 16) << 8)) + ((~s & 1) * 512 + head * 16 + 8 + r * 4)),
                       ((c0 * 5 + time_offset(t16_ & zero)) & ~31u) | ((s + 1) & 31), (t16 & 0x1E0) == 0);
        expect(bars + B_PAIR, 512);
      }
      if (w4 == 0) {
        const uint4 pl = next_plan(lds16(bars + C_T), last_stores(f, flag_ptr(G, near, t16_, s), s), s, d);
        sts16(bars + C_T, pl);
        const uint32_t tk = approach(pl.x, t16_ & zero);
        TRK(tk);
        spin_until(pl.x, tk);
        TR(9);
        fetch_mem(0);
      } else if (w4 == 2) {
        if (ATT && s >= 1) fetch_ex(s - 1);
      }
      if (PF0 == 3 && w4 >= 2) bar_sync(9, 96);
      }
      gv.prefetch(wsv);
      if (s >= 0) TRD(64 + cta);
      s = s1;
      if (s < NSEG - 1) wait_ft(bars + C_XF, (s + 1) & 1);
      if (ATT && s >= 2) wait_ft(bars + C_EX, s & 1);
      gemv_v(s, IntC<0>());
      if (s == NSEG - 1) break;
    }
  } else {
    wsv = lds4(TAB(t16_));
    vmo = 0;
#pragma unroll 1
    for (int s = UNI(zero - 2);;) {
      const int s1 = UNI(s + 1);
      if (w4 == 2 && s + 2 < NSEG) fetch_x(s + 2, 0);
      if (w4 == 3 && s + 2 + XP < NSEG) asm volatile(ELECT "cp.async.bulk.prefetch.L2.global [%0], 1024;}" ::"l"(xin + ((s + 2 + XP) * 64 + cta) * 512) : "memory");
      if (s + 2 < NSEG) vproj1(s + 2, gv, wsv); else { bar_sync(6, 160); gv.prefetch(wsv); }
      if (ATT) store_o(s - 2);
      TR(7);
      if (s >= 0) TRD(64 + cta);
      s = s1;
      if (s < 0) {
        bar_arrive(4, 256);
        reader_side();
        wsv = lds4(TAB(t16_));
        continue;
      }
      gemv_v(s, IntC<1>());
      if (s == NSEG - 1) break;
      if (ATT && s >= 2) attention(s - 2, true); else if (PVG) bar_sync(7, 160);
      pre_o();
      TR(2);
      gemv_o(s, IntC<1>(), [](uint32_t) {});
      TR(5);
      bar_arrive(3, 256);
      if (ATT) asm volatile("fence.proxy.async.shared::cta;" ::: "memory");
    }
  }
  if (ATT) {
    asm volatile("fence.proxy.async.shared::cta;" ::: "memory");
    __syncthreads();
#pragma unroll 1
    for (int n = NSEG - 3; n < NSEG; n++) {
      if (warp == 1 && n > NSEG - 3) {
        const char* fl = flag_ptr(G, near, t16_, NSEG - 1);
        last_stores(ld_relaxed16(fl), fl, NSEG - 1);
        fetch_ex(n);
      }
      if (wg) {
        wait_ft(bars + C_EX, n & 1);
        attention(n, false);
        asm volatile("fence.proxy.async.shared::cta;" ::: "memory");
        __syncwarp();
        store_o(n);
      }
    }
  }
  if (wg) {
    asm volatile("cp.async.bulk.wait_group 0;" ::: "memory");
    __syncwarp();
    if (lane == 0) { __threadfence(); atomicAdd(&g_rings.ctr[3][0], 1); }
  }
  __syncwarp();
  cluster_sync();
  if (tid == 0) STAMP(2);
}
template <int CS>
__global__ void __launch_bounds__(256, 1)
vo_kernel(const __grid_constant__ CUtensorMap tmWv, const __grid_constant__ CUtensorMap tmWo, const __grid_constant__ CUtensorMap tmX,
          const __grid_constant__ CUtensorMap tmU, const bf16* __restrict__ mem0, const bf16* __restrict__ xin, char* __restrict__ G, const Pace d, int zero) {
  vo_body<CS>(tmWv, tmWo, tmX, tmU, mem0, xin, G, d, zero, blockIdx.x);
}

__device__ uint32_t g_z1[512 * S_LEN];
__device__ uint32_t g_z2[512 * S_LEN];
__device__ __align__(16) uint32_t g_wt[513 * S_LEN];

__device__ __forceinline__ float2 cmul(float2 a, float2 b) { return make_float2(fmaf(a.x, b.x, -a.y * b.y), fmaf(a.x, b.y, a.y * b.x)); }
__device__ __forceinline__ float2 unpack_bf16(uint32_t v) { return make_float2(__uint_as_float(v << 16), __uint_as_float(v & 0xFFFF0000u)); }
__host__ __device__ constexpr float cos32(int i) {
  return i == 0 ? 1.f : i == 1 ? 0.98078528040323044913f : i == 2 ? 0.92387953251128675613f : i == 3 ? 0.83146961230254523708f
       : i == 4 ? 0.70710678118654752440f : i == 5 ? 0.55557023301960222474f : i == 6 ? 0.38268343236508977173f
       : i == 7 ? 0.19509032201612826785f : 0.f;
}
template <int I, int DIR> __device__ __forceinline__ float2 rot32(float2 v) {
  if constexpr (I == 0) return v;
  else if constexpr (I == 8) return DIR > 0 ? make_float2(-v.y, v.x) : make_float2(v.y, -v.x);
  else {
    constexpr float cs = I < 8 ? cos32(I) : -cos32(16 - I);
    constexpr float sn = (I < 8 ? cos32(8 - I) : cos32(I - 8)) * DIR;
    if constexpr (I == 4 || I == 12) {
      constexpr float sgn = (cs > 0) == (sn > 0) ? 1.f : -1.f;
      return make_float2(cs * (v.x - sgn * v.y), cs * (v.y + sgn * v.x));
    } else return make_float2(fmaf(v.x, cs, -v.y * sn), fmaf(v.x, sn, v.y * cs));
  }
}
template <int N, int DIR, int K> struct Comb {
  static __device__ __forceinline__ void run(const float2* e, const float2* o, float2* out) {
    if constexpr (K < N / 2) {
      const float2 t = rot32<K * (32 / N), DIR>(o[K]);
      out[K] = make_float2(e[K].x + t.x, e[K].y + t.y);
      out[K + N / 2] = make_float2(e[K].x - t.x, e[K].y - t.y);
      Comb<N, DIR, K + 1>::run(e, o, out);
    }
  }
};
template <int N, int DIR, int ST> __device__ __forceinline__ void fft_r(const float2* in, float2* out) {
  if constexpr (N == 1) out[0] = in[0];
  else {
    float2 e[N / 2], o[N / 2];
    fft_r<N / 2, DIR, ST * 2>(in, e);
    fft_r<N / 2, DIR, ST * 2>(in + ST, o);
    Comb<N, DIR, 0>::run(e, o, out);
  }
}
template <int N, int DIR> __device__ __forceinline__ void fft_reg(float2* v) {
  float2 t[N];
  fft_r<N, DIR, 1>(v, t);
#pragma unroll
  for (int i = 0; i < N; i++) v[i] = t[i];
}
template <int N> __device__ __forceinline__ void twiddle(float2* v, float x) {
  float2 p[N];
  sincospif(x, &p[1].y, &p[1].x);
#pragma unroll
  for (int k = 2; k < N; k++) p[k] = cmul(p[k / 2], p[k - k / 2]);
#pragma unroll
  for (int k = 1; k < N; k++) v[k] = cmul(v[k], p[k]);
}

constexpr int F1_LD = 16 * 33 - 1;
constexpr int F1_SMEM = 16 * F1_LD * 8;
__device__ __forceinline__ void fft_rows_fwd(float2* fs, int item, const bf16* __restrict__ x, const bf16* __restrict__ wr, const bf16* __restrict__ wi) {
  const int tid = threadIdx.x, s0 = item * 16;
  {
    const int row = tid >> 4, t = tid & 15;
    const uint2* src = reinterpret_cast<const uint2*>(x + (size_t)(s0 + row) * DM) + t;
    float2 a[16], b[16];
#pragma unroll
    for (int i = 0; i < 16; i++) { const uint2 v = __ldg(src + i * 16); a[i] = unpack_bf16(v.x); b[i] = unpack_bf16(v.y); }
    fft_reg<16, -1>(a); twiddle<16>(a, -(float)(2 * t) / 256.f);
    float2* d = fs + row * F1_LD + t;
#pragma unroll
    for (int i = 0; i < 16; i++) d[i * 33] = a[i];
    fft_reg<16, -1>(b); twiddle<16>(b, -(float)(2 * t + 1) / 256.f);
#pragma unroll
    for (int i = 0; i < 16; i++) d[i * 33 + 16] = b[i];
  }
  __syncthreads();
  {
    const int row = tid & 15, k2 = tid >> 4;
    float2 v[32];
#pragma unroll
    for (int i = 0; i < 32; i++) v[i] = fs[row * F1_LD + k2 * 33 + (i >> 1) + (i & 1) * 16];
    fft_reg<32, -1>(v);
#pragma unroll
    for (int i = 0; i < 32; i++) g_z1[(k2 + 16 * i) * S_LEN + s0 + row] = pack_bf16(v[i].x, v[i].y);
  }
  {
    __syncthreads();
    uint4* sw = reinterpret_cast<uint4*>(fs);
    const uint4* pr = reinterpret_cast<const uint4*>(wr + (size_t)s0 * 513);
    const uint4* pi = reinterpret_cast<const uint4*>(wi + (size_t)s0 * 513);
#pragma unroll
    for (int q = 0; q < 5; q++) {
      const int i = tid + q * 256;
      if (i < 1026) { sw[i] = __ldg(pr + i); sw[1026 + i] = __ldg(pi + i); }
    }
    __syncthreads();
    const uint16_t* hr = reinterpret_cast<const uint16_t*>(fs) + (tid & 3) * 4 * 513;
    const uint16_t* hi = hr + 1026 * 8;
#pragma unroll
    for (int q = 0; q < 9; q++) {
      const int k = (tid >> 2) + q * 64;
      if (q == 8 && k != 512) break;
      uint32_t o[4];
#pragma unroll
      for (int r = 0; r < 4; r++) o[r] = (uint32_t)hr[r * 513 + k] | ((uint32_t)hi[r * 513 + k] << 16);
      *reinterpret_cast<uint4*>(g_wt + k * S_LEN + s0 + (tid & 3) * 4) = make_uint4(o[0], o[1], o[2], o[3]);
    }
  }
}

constexpr int F2_LD = 2048 + 128;
__device__ __forceinline__ int f2_pad(int i) { return i + (i >> 7); }
__device__ __forceinline__ void fft_cols(float2* fs, int item) {
  const int tid = threadIdx.x, half = tid >> 7, t = tid & 127;
  const int k = item == 0 ? half * 256 : (half ? 512 - item : item);
  float2* my = fs + half * F2_LD;
  const float2* mir = fs + (item == 0 ? half : half ^ 1) * F2_LD;
  float2 v[16];
#pragma unroll
  for (int a = 0; a < 16; a++) v[a] = unpack_bf16(__ldcg(&g_z1[k * S_LEN + t + 128 * a]));
  fft_reg<16, -1>(v); twiddle<16>(v, -(float)t / 1024.f);
#pragma unroll
  for (int i = 0; i < 16; i++) my[f2_pad(i * 128 + t)] = v[i];
  bar_sync(1 + half, 128);
  const int t0 = t & 15, kp = t >> 4;
#pragma unroll
  for (int h = 0; h < 2; h++) {
#pragma unroll
    for (int b = 0; b < 8; b++) v[h * 8 + b] = my[f2_pad((2 * kp + h) * 128 + t0 + 16 * b)];
    fft_reg<8, -1>(v + h * 8);
  }
  float2 p8[8];
  sincospif(-(float)t0 / 64.f, &p8[1].y, &p8[1].x);
#pragma unroll
  for (int i = 2; i < 8; i++) p8[i] = cmul(p8[i / 2], p8[i - i / 2]);
#pragma unroll
  for (int h = 0; h < 2; h++)
#pragma unroll
    for (int b = 0; b < 8; b++)
      my[f2_pad((2 * kp + h) * 128 + t0 + 16 * b)] = b ? cmul(v[h * 8 + b], p8[b]) : v[h * 8];
  uint32_t wa[16], wb[16];
#pragma unroll
  for (int m = 0; m < 16; m++) {
    wa[m] = __ldcg(&g_wt[k * S_LEN + t + 128 * m]);
    wb[m] = __ldcg(&g_wt[(512 - k) * S_LEN + ((2048 - t - 128 * m) & 2047)]);
  }
  bar_sync(1 + half, 128);
  const int base3 = (t & 15) * 128 + (t >> 4) * 16;
#pragma unroll
  for (int i = 0; i < 16; i++) v[i] = my[f2_pad(base3 + i)];
  fft_reg<16, -1>(v);
  bar_sync(1 + half, 128);
#pragma unroll
  for (int m = 0; m < 16; m++) my[t + 128 * m] = v[m];
  __syncthreads();
  {
    float sn, cs;
    sincospif((float)k / 512.f, &sn, &cs);
    const float sc = 0.5f / (2048.f * 512.f);
#pragma unroll
    for (int m = 0; m < 16; m++) {
      const int j = t + 128 * m, jm = (2048 - j) & 2047;
      float2 A = unpack_bf16(wa[m]), B = unpack_bf16(wb[m]);
      B.y = -B.y;
      if (k == 0) {
        const float2 A2 = unpack_bf16(__ldcg(&g_wt[jm])), B2 = unpack_bf16(__ldcg(&g_wt[512 * S_LEN + j]));
        A = make_float2(0.5f * (A.x + A2.x), 0.5f * (A.y - A2.y));
        B = make_float2(0.5f * (B.x + B2.x), 0.5f * (B.y + B2.y));
      }
      const float2 df = make_float2((A.x - B.x) * sc, (A.y - B.y) * sc);
      const float2 ca = make_float2(fmaf(-sn, df.x, (A.x + B.x) * sc), fmaf(-sn, df.y, (A.y + B.y) * sc));
      const float2 cb = make_float2(-cs * df.y, cs * df.x);
      float2 zc = mir[jm];
      zc.y = -zc.y;
      const float2 r1 = cmul(ca, v[m]), r2 = cmul(cb, zc);
      v[m] = make_float2(r1.x + r2.x, r1.y + r2.y);
    }
  }
  fft_reg<16, 1>(v);
  __syncthreads();
#pragma unroll
  for (int i = 0; i < 16; i++) my[f2_pad(base3 + i)] = v[i];
  bar_sync(1 + half, 128);
#pragma unroll
  for (int h = 0; h < 2; h++) {
#pragma unroll
    for (int b = 0; b < 8; b++) {
      const float2 z = my[f2_pad((2 * kp + h) * 128 + t0 + 16 * b)];
      v[h * 8 + b] = b ? cmul(z, make_float2(p8[b].x, -p8[b].y)) : z;
    }
    fft_reg<8, 1>(v + h * 8);
#pragma unroll
    for (int b = 0; b < 8; b++) my[f2_pad((2 * kp + h) * 128 + t0 + 16 * b)] = v[h * 8 + b];
  }
  bar_sync(1 + half, 128);
#pragma unroll
  for (int i = 0; i < 16; i++) v[i] = my[f2_pad(i * 128 + t)];
  twiddle<16>(v, (float)t / 1024.f);
  fft_reg<16, 1>(v);
#pragma unroll
  for (int a = 0; a < 16; a++) g_z2[k * S_LEN + t + 128 * a] = pack_bf16(v[a].x, v[a].y);
}

__device__ __forceinline__ void fft_rows_inv(float2* fs, int item, bf16* __restrict__ out) {
  const int tid = threadIdx.x, s0 = item * 16;
  {
    const int row = tid & 15, k2 = tid >> 4;
    float2 v[32];
#pragma unroll
    for (int i = 0; i < 32; i++) v[i] = unpack_bf16(__ldcg(&g_z2[(k2 + 16 * i) * S_LEN + s0 + row]));
    fft_reg<32, 1>(v);
#pragma unroll
    for (int i = 0; i < 32; i++) fs[row * F1_LD + k2 * 33 + (i >> 1) + (i & 1) * 16] = v[i];
  }
  __syncthreads();
  {
    const int row = tid >> 4, t = tid & 15;
    const float2* d = fs + row * F1_LD + t;
    float2 a[16], b[16];
#pragma unroll
    for (int i = 0; i < 16; i++) { a[i] = d[i * 33]; b[i] = d[i * 33 + 16]; }
    twiddle<16>(a, (float)(2 * t) / 256.f); fft_reg<16, 1>(a);
    twiddle<16>(b, (float)(2 * t + 1) / 256.f); fft_reg<16, 1>(b);
    uint2* dst = reinterpret_cast<uint2*>(out + (size_t)(s0 + row) * OUT_LD) + t;
#pragma unroll
    for (int i = 0; i < 16; i++) dst[i * 16] = make_uint2(pack_bf16(a[i].x, a[i].y), pack_bf16(b[i].x, b[i].y));
  }
}

__global__ void __maxnreg__(112) fft_all(const bf16* __restrict__ x, const bf16* __restrict__ wr, const bf16* __restrict__ wi, bf16* __restrict__ out) {
  extern __shared__ float2 fs[];
  volatile int& s_item = *reinterpret_cast<volatile int*>(fs + 15 * F1_LD + 14 * 33 + 32);
  asm volatile("griddepcontrol.launch_dependents;" ::: "memory");
  int* ctr = &g_rings.ctr[0][0];
  int phase = 0, cnt = 0;
  for (;;) {
    __syncthreads();
    if (threadIdx.x == 0) {
      const int it = atomicAdd(ctr, 1) + 1;
      const int ph = (it >= 128) + (it >= 384) + (it >= 512);
      if (ph != phase) {
        if (cnt) { __threadfence(); atomicAdd(ctr + 32 + phase * 32, cnt); }
        const int target = ph == 1 ? 127 : 255;
        for (int i = 0; ph < 3 && i < (1 << 22); i++) {
          int v; asm volatile("ld.acquire.gpu.global.s32 %0, [%1];" : "=r"(v) : "l"(ctr + ph * 32) : "memory");
          if (v == target) break;
          __nanosleep(100);
        }
        phase = ph; cnt = 0;
      }
      cnt += ph < 2;
      if (it == 128) STAMP(5);
      if (it == 384) STAMP(6);
      if (it >= 512) STAMP(7);
      s_item = it;
    }
    __syncthreads();
    const int it = s_item;
    if (it >= 512) break;
    if (it < 128) {
      const int nx = it + (int)gridDim.x;
      if (nx < 128) {
        asm volatile("prefetch.global.L2 [%0];" ::"l"(x + (size_t)nx * 16 * DM + threadIdx.x * 64));
        asm volatile("prefetch.global.L2 [%0];" ::"l"((threadIdx.x < 128 ? wr : wi) + (size_t)nx * 16 * 513 + (threadIdx.x & 127) * 64));
      }
      fft_rows_fwd(fs, it, x, wr, wi);
    }
    else if (it < 384) fft_cols(fs, it - 128);
    else fft_rows_inv(fs, it - 384, out);
  }
  if (blockIdx.x == 0) asm volatile("griddepcontrol.wait;" ::: "memory");
}

typedef CUresult (*EncodeFn)(CUtensorMap*, CUtensorMapDataType, cuuint32_t, void*, const cuuint64_t*, const cuuint64_t*,
                             const cuuint32_t*, const cuuint32_t*, CUtensorMapInterleave, CUtensorMapSwizzle,
                             CUtensorMapL2promotion, CUtensorMapFloatOOBfill);
static EncodeFn g_encode;
static bool g_big;
static CUtensorMap make_map(const void* p, uint64_t cols, uint64_t rows, uint64_t ld, uint32_t bc, uint32_t br, bool swz) {
  CUtensorMap m;
  cuuint64_t dims[2] = {cols, rows}, st[1] = {ld * 2};
  cuuint32_t box[2] = {bc, br}, es[2] = {1, 1};
  g_encode(&m, CU_TENSOR_MAP_DATA_TYPE_BFLOAT16, 2, const_cast<void*>(p), dims, st, box, es, CU_TENSOR_MAP_INTERLEAVE_NONE,
           swz ? CU_TENSOR_MAP_SWIZZLE_128B : CU_TENSOR_MAP_SWIZZLE_NONE, CU_TENSOR_MAP_L2_PROMOTION_L2_256B,
           CU_TENSOR_MAP_FLOAT_OOB_FILL_NONE);
  return m;
}
template <typename... KA, typename... A>
static void launch(void (*k)(KA...), dim3 grid, dim3 block, size_t smem, int cluster, bool pdl, cudaStream_t st, A... args) {
  cudaLaunchConfig_t cfg = {};
  cfg.gridDim = grid; cfg.blockDim = block; cfg.dynamicSmemBytes = smem; cfg.stream = st;
  cudaLaunchAttribute at[2]; int n = 0;
  if (cluster > 1) { at[n].id = cudaLaunchAttributeClusterDimension; at[n].val.clusterDim.x = cluster; at[n].val.clusterDim.y = 1; at[n].val.clusterDim.z = 1; n++; }
  if (pdl) { at[n].id = cudaLaunchAttributeProgrammaticStreamSerialization; at[n].val.programmaticStreamSerializationAllowed = 1; n++; }
  cfg.attrs = at; cfg.numAttrs = n;
  cudaLaunchKernelEx(&cfg, k, args...);
}
#define PARAM(n, d) (d)

#define ACS 8
#define VCS 8
extern "C" void kernel_launch(void* const* d_in, const int* in_sizes, int n_in, void* d_out, int out_size) {
  const bf16* Ax = (const bf16*)d_in[0]; const bf16* Awr = (const bf16*)d_in[1]; const bf16* Awi = (const bf16*)d_in[2];
  const bf16* Bx = (const bf16*)d_in[3]; const bf16* mem0 = (const bf16*)d_in[4];
  const bf16* Wq = (const bf16*)d_in[5]; const bf16* Wk = (const bf16*)d_in[6]; const bf16* Wv = (const bf16*)d_in[7];
  const bf16* Wo = (const bf16*)d_in[8];
  bf16* out = (bf16*)d_out;
  if (!g_encode) {
    cudaDriverEntryPointQueryResult qr;
    cudaGetDriverEntryPoint("cuTensorMapEncodeTiled", (void**)&g_encode, cudaEnableDefault, &qr);
    cudaFuncSetAttribute(gemm_kernel, cudaFuncAttributeMaxDynamicSharedMemorySize, G_SMEM);
    cudaFuncSetAttribute(qk_kernel, cudaFuncAttributeMaxDynamicSharedMemorySize, A_SMEM);
    cudaFuncSetAttribute(vo_kernel<VCS>, cudaFuncAttributeMaxDynamicSharedMemorySize, V_SMEM);
    cudaFuncSetAttribute(vo_kernel<2>, cudaFuncAttributeMaxDynamicSharedMemorySize, V_SMEM);
    cudaLaunchConfig_t cfg = {};
    cfg.gridDim = dim3(64); cfg.blockDim = dim3(256); cfg.dynamicSmemBytes = V_SMEM;
    cudaLaunchAttribute at;
    at.id = cudaLaunchAttributeClusterDimension; at.val.clusterDim.x = VCS; at.val.clusterDim.y = 1; at.val.clusterDim.z = 1;
    cfg.attrs = &at; cfg.numAttrs = 1;
    int n = 0;
    g_big = cudaOccupancyMaxActiveClusters(&n, vo_kernel<VCS>, &cfg) == cudaSuccess && n * VCS >= 120;
    cudaFuncSetAttribute(fft_all, cudaFuncAttributeMaxDynamicSharedMemorySize, F1_SMEM);
  }
  void *p_ux, *p_rings, *p_win;
  cudaGetSymbolAddress(&p_ux, g_ux); cudaGetSymbolAddress(&p_rings, g_rings); cudaGetSymbolAddress(&p_win, g_win);
  char* win = (char*)(((uintptr_t)p_win + (2u << 20) - 1) & ~(uintptr_t)((2u << 20) - 1));
  const CUtensorMap rWq = make_map(Wq, HD, DM, HD, 64, 128, true), rWk = make_map(Wk, HD, DM, HD, 64, 128, true),
                    rWv = make_map(Wv, HD, DM, HD, 64, 128, true), rWo = make_map(Wo, DM, HD, DM, 32, 128, false);
  CUtensorMap rX[3];
  for (int i = 0; i < 3; i++) {
    cuuint64_t dims[3] = {64, S_LEN, 16}, st[2] = {DM * 2, 128};
    cuuint32_t box[3] = {64, 32, i == 0 ? 4u : i == 1 ? 8u / VCS : 8u / ACS}, es[3] = {1, 1, 1};
    g_encode(&rX[i], CU_TENSOR_MAP_DATA_TYPE_BFLOAT16, 3, const_cast<bf16*>(Bx), dims, st, box, es, CU_TENSOR_MAP_INTERLEAVE_NONE,
             CU_TENSOR_MAP_SWIZZLE_128B, CU_TENSOR_MAP_L2_PROMOTION_L2_256B, CU_TENSOR_MAP_FLOAT_OOB_FILL_NONE);
  }
  const CUtensorMap mU = make_map(p_ux, HD, S_LEN, HD, 64, 64, true), mWo = make_map(Wo, DM, HD, DM, 64, 64, true);
  const CUtensorMap sU = make_map(p_ux, HD, S_LEN, HD, 64, 8, true);
  const CUtensorMap mOut = make_map(out, OUT_LD, S_LEN, OUT_LD, 64, 64, true);
  cudaStream_t st = cudaStreamPerThread;
  const Pace pace = {5 * PARAM("F0", 2100), 5 * PARAM("U0", 2750), 10 * (PARAM("M0", 2050) / 2), 5 * PARAM("MU", 90), 5 * PARAM("MM", 100), 5 * PARAM("DOK", -10), 5 * PARAM("DL", 900),
                     5 * PARAM("DEC", 6), 5 * PARAM("CAP", 60), 5 * PARAM("DS", 200), 5 * PARAM("DC", 800)};
  if (g_big) launch(vo_kernel<VCS>, dim3(64), dim3(256), V_SMEM, VCS, false, st, rWv, rWo, rX[1], sU, mem0, Bx, win, pace, 0);
  else launch(vo_kernel<2>, dim3(64), dim3(256), V_SMEM, 2, false, st, rWv, rWo, rX[0], sU, mem0, Bx, win, pace, 0);
  const int nbig = g_big && ACS > 2 ? 56 : 0;
  if (nbig) launch(qk_kernel, dim3(nbig), dim3(256), A_SMEM, ACS, true, st, rWq, rWk, rX[2], win, pace, 0, 0, ACS);
  launch(qk_kernel, dim3(64 - nbig), dim3(256), A_SMEM, 2, true, st, rWq, rWk, rX[0], win, pace, 0, nbig, 2);
  if (PARAM("BG", 8)) launch(fft_all, dim3(PARAM("BG", 8)), dim3(256), F1_SMEM, 1, true, st, Ax, Awr, Awi, out);
  launch(gemm_kernel, dim3(8, 16), dim3(288), G_SMEM, 2, true, st, mU, mWo, mWo, mWo, mOut, 8, 64, 1024, (const int*)((char*)p_rings + offsetof(Rings, ctr) + 3 * 128));
  if (PARAM("TAIL", 128)) launch(fft_all, dim3(PARAM("TAIL", 128)), dim3(256), F1_SMEM, 1, true, st, Ax, Awr, Awi, out);
}
```
